```python
import torch

def _softmax(x, axis=-1):
    return torch.softmax(x, dim=axis)
def _gelu(x):
    return torch.nn.functional.gelu(x, approximate="tanh")
def _silu(x):
    return torch.nn.functional.silu(x)
def _sigmoid(x):
    return torch.sigmoid(x)
def _layernorm(x, axis=-1, eps=1e-5):
    m = x.mean(dim=axis, keepdim=True)
    v = x.var(dim=axis, keepdim=True, unbiased=False)
    return (x - m) / torch.sqrt(v + eps)
def _scatter_add(tgt, idx, src, axis=0):
    return tgt.clone().index_add_(axis, idx, src)
def _segment_sum(src, seg, n):
    out = torch.zeros((n,) + src.shape[1:], dtype=src.dtype)
    return out.index_add_(0, seg, src)
def _pad(x, pw):
    flat = tuple(v for pair in reversed(pw) for v in pair)
    return torch.nn.functional.pad(x, flat)

kernel_name = 'parallel_sum__sliding_local_dilated__glu_gated_glu__prompt'

def setup_inputs():

    _w = (lambda a: (lambda t: t.to(torch.bfloat16) if t.is_floating_point() else t)(torch.as_tensor(a)))
    def _A_setup():
        B, S, D = 1, 2048, 576
        return {
            "x": _w((lambda *s: torch.randn(*s, dtype=torch.bfloat16) * 0.05)(B, S, D)),
            "wqkv": _w((lambda *s: torch.randn(*s, dtype=torch.bfloat16) * 0.05)(D, 3 * D)),
            "wo": _w((lambda *s: torch.randn(*s, dtype=torch.bfloat16) * 0.05)(D, D)),
        }
    _A_in = _A_setup()

    def _B_setup():
        B, S, D, F = 1, 2048, 576, 4608
        return {
            "x": _w((lambda *s: torch.randn(*s, dtype=torch.bfloat16) * 0.05)(B, S, D)),
            "w_gate": _w((lambda *s: torch.randn(*s, dtype=torch.bfloat16) * 0.05)(D, F)),
            "w_up": _w((lambda *s: torch.randn(*s, dtype=torch.bfloat16) * 0.05)(D, F)),
            "w_down": _w((lambda *s: torch.randn(*s, dtype=torch.bfloat16) * 0.05)(F, D)),
        }
    _B_in = _B_setup()

    return {
        "A_x": _A_in["x"],
        "A_wqkv": _A_in["wqkv"],
        "A_wo": _A_in["wo"],
        "B_x": _B_in["x"],
        "B_w_gate": _B_in["w_gate"],
        "B_w_up": _B_in["w_up"],
        "B_w_down": _B_in["w_down"],
    }

def reference(A_x, A_wqkv, A_wo, B_x, B_w_gate, B_w_up, B_w_down):
    def _A_ref(x, wqkv, wo):
        B, S, D = x.shape
        H = 32; Dh = D // H
        W, dil = 8, 2
        qkv = (lambda x, *d: x.permute(*d))((x @ wqkv).reshape(B, S, 3, H, Dh), 2, 0, 3, 1, 4)
        q, k, v = qkv[0], qkv[1], qkv[2]
        scale = Dh ** -0.5
        pos = torch.arange(S)
        off = torch.arange(W) * dil
        idx = pos[:, None] - off[None, :]
        mask = idx >= 0
        idx_c = torch.where(mask, idx, 0).reshape(-1)
        kg = k[:, :, idx_c, :].reshape(B, H, S, W, Dh)
        vg = v[:, :, idx_c, :].reshape(B, H, S, W, Dh)
        logits = torch.einsum("bhsd,bhswd->bhsw", q, kg) * scale
        logits = torch.where(mask[None, None, :, :], logits, -1e9)
        attn = _softmax(logits, axis=-1)
        o = torch.einsum("bhsw,bhswd->bhsd", attn, vg)
        return (lambda x, *d: x.permute(*d))(o, 0, 2, 1, 3).reshape(B, S, D) @ wo

    def _B_ref(x, w_gate, w_up, w_down):
        g = torch.einsum("bsd,df->bsf", x, w_gate)
        u = torch.einsum("bsd,df->bsf", x, w_up)
        h = _sigmoid(g) * u
        return torch.einsum("bsf,fd->bsd", h, w_down)

    x = A_x
    xn = _layernorm(x, axis=-1)
    return x + _A_ref(xn, A_wqkv, A_wo) + _B_ref(xn, B_w_gate, B_w_up, B_w_down)
```

```cpp
#include <cuda_runtime.h>
#include <cuda.h>
#include <cuda_bf16.h>
#include <stdint.h>
#include <type_traits>

namespace {

constexpr int SEQ = 2048, DM = 576, FF = 4608;
constexpr int SLOT = 18432, NSLOT = 9;
constexpr int QPITCH = 432;
constexpr int OFF_HALO = 9 * SLOT;
constexpr int OFF_QKV = OFF_HALO + 14 * QPITCH;
constexpr int OFF_AST = 9 * SLOT, AST_WARP = 7680;
constexpr int OFF_AX = 12 * SLOT + 6144;
constexpr int OFF_BAR = OFF_AX + 4096;
constexpr int BAR_FULL = 0, BAR_EMPTY = 96, BAR_DEPH = 192, BAR_XDONE = 200, BAR_ATTN = 208, BAR_QKV = 240, BAR_HDONE = 248, BAR_DEPS = 256,
              BAR_DRAIN = 264, OFF_EPOCH = 280;
constexpr int SMEM_BYTES = OFF_BAR + 320 + 624;
static_assert(SMEM_BYTES <= 232448 && OFF_QKV + 128 * QPITCH <= OFF_AX, "smem");
constexpr int NP2 = 81;
#define PP_KB 2
#define WDEPTH 2
#define P2T 0
#define LAGJ 3
#define HOLD_KB 3
#define PF2 0
#define PF3 0
#define TLBW 1
#define PP_KB0 5
#define PP_KB1 5
constexpr unsigned SPIN_LIMIT = 1u << 26;

__device__ uint4 g_a2[16 * 4 * NP2 * 256];
__device__ uint4 g_halo[16 * 8 * 14 * 18];
__device__ unsigned g_flag_halo[128], g_flag_o[128], g_flag_h[128];
__device__ unsigned g_ctr;

#define TM(role, i)
#define TMG(role, i)
#define TMDUMP(role)
#define TMZERO()

__device__ __forceinline__ uint32_t smem_u32(const void* p) { return (uint32_t)__cvta_generic_to_shared(p); }
__device__ __forceinline__ void mbar_init(uint32_t bar, uint32_t cnt) {
  asm volatile("mbarrier.init.shared::cta.b64 [%0], %1;" ::"r"(bar), "r"(cnt) : "memory");
}
__device__ __forceinline__ void mbar_expect_tx(uint32_t bar, uint32_t bytes) {
  asm volatile("mbarrier.arrive.expect_tx.shared::cta.b64 _, [%0], %1;" ::"r"(bar), "r"(bytes) : "memory");
}
__device__ __forceinline__ void mbar_arrive(uint32_t bar) {
  asm volatile("mbarrier.arrive.shared::cta.b64 _, [%0];" ::"r"(bar) : "memory");
}
__device__ __forceinline__ void mbar_arrive_cl(uint32_t bar, uint32_t cnt) {
  asm volatile("mbarrier.arrive.shared::cluster.b64 _, [%0], %1;" ::"r"(bar), "r"(cnt) : "memory");
}
__device__ __forceinline__ uint32_t mapa(uint32_t addr, uint32_t cta) {
  uint32_t r; asm("mapa.shared::cluster.u32 %0, %1, %2;" : "=r"(r) : "r"(addr), "r"(cta)); return r;
}
__device__ __forceinline__ void mbar_wait(uint32_t bar, uint32_t parity) {
  asm volatile(
      "{\n"
      ".reg .pred p;\n"
      ".reg .u32 n;\n"
      "mov.u32 n, 0;\n"
      "WAIT_LOOP:\n"
      "mbarrier.try_wait.parity.shared::cta.b64 p, [%0], %1;\n"
      "@p bra WAIT_DONE;\n"
      "add.u32 n, n, 1;\n"
      "setp.lt.u32 p, n, %2;\n"
      "@p bra WAIT_LOOP;\n"
      "trap;\n"
      "WAIT_DONE:\n"
      "}\n" ::"r"(bar), "r"(parity), "n"(1u << 22) : "memory");
}
__device__ __forceinline__ bool elect_one() {
  uint32_t p;
  asm volatile("{ .reg .pred q; elect.sync _|q, 0xffffffff; selp.u32 %0, 1, 0, q; }" : "=r"(p));
  return p;
}
__device__ __forceinline__ void tma_2d_mc(uint32_t dst, const CUtensorMap* m, int c0, int c1, uint32_t bar) {
  asm volatile("cp.async.bulk.tensor.2d.shared::cluster.global.mbarrier::complete_tx::bytes.multicast::cluster"
               " [%0], [%1, {%3, %4}], [%2], %5;"
               ::"r"(dst), "l"(m), "r"(bar), "r"(c0), "r"(c1), "h"((uint16_t)3) : "memory");
}
__device__ __forceinline__ void tma_3d_mc(uint32_t dst, const CUtensorMap* m, int c0, int c1, int c2, uint32_t bar) {
  asm volatile("cp.async.bulk.tensor.3d.shared::cluster.global.mbarrier::complete_tx::bytes.multicast::cluster"
               " [%0], [%1, {%3, %4, %5}], [%2], %6;"
               ::"r"(dst), "l"(m), "r"(bar), "r"(c0), "r"(c1), "r"(c2), "h"((uint16_t)3) : "memory");
}
__device__ __forceinline__ void tma_red_3d(const CUtensorMap* m, int c0, int c1, int c2, uint32_t src) {
  asm volatile("cp.reduce.async.bulk.tensor.3d.global.shared::cta.add.bulk_group [%0, {%2, %3, %4}], [%1];"
               ::"l"(m), "r"(src), "r"(c0), "r"(c1), "r"(c2) : "memory");
}
__device__ __forceinline__ void prefetch_map(const CUtensorMap* m) {
  asm volatile("prefetch.tensormap [%0];" ::"l"(m) : "memory");
}
__device__ __forceinline__ void l2_prefetch_line(const void* p) { asm volatile("prefetch.global.L2 [%0];" ::"l"(p) : "memory"); }
__device__ __forceinline__ void cp_async16(uint32_t dst, const void* src) {
  asm volatile("cp.async.cg.shared.global [%0], [%1], 16;" ::"r"(dst), "l"(src) : "memory");
}
__device__ __forceinline__ void wg_fence() { asm volatile("wgmma.fence.sync.aligned;" ::: "memory"); }
__device__ __forceinline__ void wg_commit() { asm volatile("wgmma.commit_group.sync.aligned;" ::: "memory"); }
template <int N> __device__ __forceinline__ void wg_wait() { asm volatile("wgmma.wait_group.sync.aligned %0;" ::"n"(N) : "memory"); }
template <int N> __device__ __forceinline__ void keep(float* d) {
#pragma unroll
  for (int i = 0; i < N; i++) asm volatile("" : "+f"(d[i])::"memory");
}
__device__ __forceinline__ void named_sync(int id, int n) { asm volatile("bar.sync %0, %1;" ::"r"(id), "r"(n) : "memory"); }
__device__ __forceinline__ void named_arrive(int id, int n) { asm volatile("bar.arrive %0, %1;" ::"r"(id), "r"(n) : "memory"); }
__device__ __forceinline__ uint32_t pack2(float lo, float hi) {
  uint32_t r; asm("cvt.rn.bf16x2.f32 %0, %1, %2;" : "=r"(r) : "f"(hi), "f"(lo)); return r;
}
__device__ __forceinline__ float blo(uint32_t v) { return __uint_as_float(v << 16); }
__device__ __forceinline__ float bhi(uint32_t v) { return __uint_as_float(v & 0xffff0000u); }
__device__ __forceinline__ uint32_t lds32(uint32_t a) { uint32_t v; asm volatile("ld.shared.u32 %0, [%1];" : "=r"(v) : "r"(a)); return v; }
__device__ __forceinline__ void sts32(uint32_t a, uint32_t v) { asm volatile("st.shared.u32 [%0], %1;" ::"r"(a), "r"(v) : "memory"); }
__device__ __forceinline__ uint4 lds128(uint32_t a) {
  uint4 v; asm volatile("ld.shared.v4.u32 {%0,%1,%2,%3}, [%4];" : "=r"(v.x), "=r"(v.y), "=r"(v.z), "=r"(v.w) : "r"(a)); return v;
}
__device__ __forceinline__ void sts128(uint32_t a, uint4 v) {
  asm volatile("st.shared.v4.u32 [%0], {%1,%2,%3,%4};" ::"r"(a), "r"(v.x), "r"(v.y), "r"(v.z), "r"(v.w) : "memory");
}
__device__ __forceinline__ uint4 ldg_cg(const uint4* p) {
  uint4 v; asm volatile("ld.global.cg.v4.u32 {%0,%1,%2,%3}, [%4];" : "=r"(v.x), "=r"(v.y), "=r"(v.z), "=r"(v.w) : "l"(p) : "memory"); return v;
}
__device__ __forceinline__ void flag_set(unsigned* f, unsigned v) {
  asm volatile("fence.acq_rel.gpu;\n st.relaxed.gpu.global.u32 [%0], %1;" ::"l"(f), "r"(v) : "memory");
}
__device__ __forceinline__ void flag_wait(const unsigned* f, unsigned v) {
  unsigned cur, n = 0;
  do {
    asm volatile("ld.acquire.gpu.global.u32 %0, [%1];" : "=r"(cur) : "l"(f) : "memory");
    if (++n > SPIN_LIMIT) __trap();
  } while (cur != v);
}
__device__ __forceinline__ uint32_t tid_now() { uint32_t t; asm volatile("mov.u32 %0, %%tid.x;" : "=r"(t)); return t; }
__device__ __forceinline__ float ex2(float x) { float r; asm("ex2.approx.ftz.f32 %0, %1;" : "=f"(r) : "f"(x)); return r; }
__device__ __forceinline__ float rcp(float x) { float r; asm("rcp.approx.ftz.f32 %0, %1;" : "=f"(r) : "f"(x)); return r; }
__device__ __forceinline__ float glu(float g, float u, float ke, float sd) { return u * rcp(fmaf(ex2(g * ke), sd, sd)); }
__device__ __forceinline__ void mma16816(float* c, uint32_t a0, uint32_t a1, uint32_t a2, uint32_t a3, uint32_t b0, uint32_t b1) {
  asm volatile("mma.sync.aligned.m16n8k16.row.col.f32.bf16.bf16.f32 {%0,%1,%2,%3}, {%4,%5,%6,%7}, {%8,%9}, {%0,%1,%2,%3};"
      : "+f"(c[0]), "+f"(c[1]), "+f"(c[2]), "+f"(c[3]) : "r"(a0), "r"(a1), "r"(a2), "r"(a3), "r"(b0), "r"(b1));
}
__device__ __forceinline__ uint32_t bsub2(uint32_t a, uint32_t b) { uint32_t r; asm("sub.rn.bf16x2 %0, %1, %2;" : "=r"(r) : "r"(a), "r"(b)); return r; }

__device__ __forceinline__ uint32_t desc_lo(uint32_t addr, uint32_t lbo) { return ((addr >> 4) & 0x3fff) | ((lbo >> 4) << 16); }
constexpr uint32_t HI128 = (1024 >> 4) | (1u << 30), HI64 = (512 >> 4) | (2u << 30), HI0 = (1024 >> 4);
template <int I, int N, class F> __device__ __forceinline__ void static_for(F&& f) {
  if constexpr (I < N) { f(std::integral_constant<int, I>{}); static_for<I + 1, N>(f); }
}

template <uint32_t OFF, uint32_t HI>
__device__ __forceinline__ void wgmma_n24(float* d, uint32_t a0, uint32_t a1, uint32_t a2, uint32_t a3, uint32_t dlo, int acc) {
  asm volatile("{ .reg .pred p; .reg .b32 lo; .reg .b64 ds; setp.ne.b32 p, %17, 0;\n"
    "add.u32 lo, %16, %18; mov.b64 ds, {lo, %19};\n"
    "wgmma.mma_async.sync.aligned.m64n24k16.f32.bf16.bf16 "
    "{%0, %1, %2, %3, %4, %5, %6, %7, %8, %9, %10, %11}, "
    "{%12, %13, %14, %15}, ds, p, 1, 1, 1; }"
    : "+f"(d[0]), "+f"(d[1]), "+f"(d[2]), "+f"(d[3]), "+f"(d[4]), "+f"(d[5]), "+f"(d[6]), "+f"(d[7]), "+f"(d[8]), "+f"(d[9]), "+f"(d[10]), "+f"(d[11])
    : "r"(a0), "r"(a1), "r"(a2), "r"(a3), "r"(dlo), "r"(acc), "n"(OFF >> 4), "n"(HI));
}

template <uint32_t OFF, uint32_t HI>
__device__ __forceinline__ void wgmma_n64(float* d, uint32_t a0, uint32_t a1, uint32_t a2, uint32_t a3, uint32_t dlo, int acc) {
  asm volatile("{ .reg .pred p; .reg .b32 lo; .reg .b64 ds; setp.ne.b32 p, %37, 0;\n"
    "add.u32 lo, %36, %38; mov.b64 ds, {lo, %39};\n"
    "wgmma.mma_async.sync.aligned.m64n64k16.f32.bf16.bf16 "
    "{%0, %1, %2, %3, %4, %5, %6, %7, %8, %9, %10, %11, %12, %13, %14, %15, %16, %17, %18, %19, %20, %21, %22, %23, %24, %25, %26, %27, %28, %29, %30, %31}, "
    "{%32, %33, %34, %35}, ds, p, 1, 1, 1; }"
    : "+f"(d[0]), "+f"(d[1]), "+f"(d[2]), "+f"(d[3]), "+f"(d[4]), "+f"(d[5]), "+f"(d[6]), "+f"(d[7]), "+f"(d[8]), "+f"(d[9]), "+f"(d[10]), "+f"(d[11]), "+f"(d[12]), "+f"(d[13]), "+f"(d[14]), "+f"(d[15]), "+f"(d[16]), "+f"(d[17]), "+f"(d[18]), "+f"(d[19]), "+f"(d[20]), "+f"(d[21]), "+f"(d[22]), "+f"(d[23]), "+f"(d[24]), "+f"(d[25]), "+f"(d[26]), "+f"(d[27]), "+f"(d[28]), "+f"(d[29]), "+f"(d[30]), "+f"(d[31])
    : "r"(a0), "r"(a1), "r"(a2), "r"(a3), "r"(dlo), "r"(acc), "n"(OFF >> 4), "n"(HI));
}

template <uint32_t OFF, uint32_t HI>
__device__ __forceinline__ void wgmma_n128(float* d, uint32_t a0, uint32_t a1, uint32_t a2, uint32_t a3, uint32_t dlo, int acc) {
  asm volatile("{ .reg .pred p; .reg .b32 lo; .reg .b64 ds; setp.ne.b32 p, %69, 0;\n"
    "add.u32 lo, %68, %70; mov.b64 ds, {lo, %71};\n"
    "wgmma.mma_async.sync.aligned.m64n128k16.f32.bf16.bf16 "
    "{%0, %1, %2, %3, %4, %5, %6, %7, %8, %9, %10, %11, %12, %13, %14, %15, %16, %17, %18, %19, %20, %21, %22, %23, %24, %25, %26, %27, %28, %29, %30, %31, %32, %33, %34, %35, %36, %37, %38, %39, %40, %41, %42, %43, %44, %45, %46, %47, %48, %49, %50, %51, %52, %53, %54, %55, %56, %57, %58, %59, %60, %61, %62, %63}, "
    "{%64, %65, %66, %67}, ds, p, 1, 1, 1; }"
    : "+f"(d[0]), "+f"(d[1]), "+f"(d[2]), "+f"(d[3]), "+f"(d[4]), "+f"(d[5]), "+f"(d[6]), "+f"(d[7]), "+f"(d[8]), "+f"(d[9]), "+f"(d[10]), "+f"(d[11]), "+f"(d[12]), "+f"(d[13]), "+f"(d[14]), "+f"(d[15]), "+f"(d[16]), "+f"(d[17]), "+f"(d[18]), "+f"(d[19]), "+f"(d[20]), "+f"(d[21]), "+f"(d[22]), "+f"(d[23]), "+f"(d[24]), "+f"(d[25]), "+f"(d[26]), "+f"(d[27]), "+f"(d[28]), "+f"(d[29]), "+f"(d[30]), "+f"(d[31]), "+f"(d[32]), "+f"(d[33]), "+f"(d[34]), "+f"(d[35]), "+f"(d[36]), "+f"(d[37]), "+f"(d[38]), "+f"(d[39]), "+f"(d[40]), "+f"(d[41]), "+f"(d[42]), "+f"(d[43]), "+f"(d[44]), "+f"(d[45]), "+f"(d[46]), "+f"(d[47]), "+f"(d[48]), "+f"(d[49]), "+f"(d[50]), "+f"(d[51]), "+f"(d[52]), "+f"(d[53]), "+f"(d[54]), "+f"(d[55]), "+f"(d[56]), "+f"(d[57]), "+f"(d[58]), "+f"(d[59]), "+f"(d[60]), "+f"(d[61]), "+f"(d[62]), "+f"(d[63])
    : "r"(a0), "r"(a1), "r"(a2), "r"(a3), "r"(dlo), "r"(acc), "n"(OFF >> 4), "n"(HI));
}

template <uint32_t OFF, uint32_t HI>
__device__ __forceinline__ void wgmma_n160(float* d, uint32_t a0, uint32_t a1, uint32_t a2, uint32_t a3, uint32_t dlo, int acc) {
  asm volatile("{ .reg .pred p; .reg .b32 lo; .reg .b64 ds; setp.ne.b32 p, %85, 0;\n"
    "add.u32 lo, %84, %86; mov.b64 ds, {lo, %87};\n"
    "wgmma.mma_async.sync.aligned.m64n160k16.f32.bf16.bf16 "
    "{%0, %1, %2, %3, %4, %5, %6, %7, %8, %9, %10, %11, %12, %13, %14, %15, %16, %17, %18, %19, %20, %21, %22, %23, %24, %25, %26, %27, %28, %29, %30, %31, %32, %33, %34, %35, %36, %37, %38, %39, %40, %41, %42, %43, %44, %45, %46, %47, %48, %49, %50, %51, %52, %53, %54, %55, %56, %57, %58, %59, %60, %61, %62, %63, %64, %65, %66, %67, %68, %69, %70, %71, %72, %73, %74, %75, %76, %77, %78, %79}, "
    "{%80, %81, %82, %83}, ds, p, 1, 1, 1; }"
    : "+f"(d[0]), "+f"(d[1]), "+f"(d[2]), "+f"(d[3]), "+f"(d[4]), "+f"(d[5]), "+f"(d[6]), "+f"(d[7]), "+f"(d[8]), "+f"(d[9]), "+f"(d[10]), "+f"(d[11]), "+f"(d[12]), "+f"(d[13]), "+f"(d[14]), "+f"(d[15]), "+f"(d[16]), "+f"(d[17]), "+f"(d[18]), "+f"(d[19]), "+f"(d[20]), "+f"(d[21]), "+f"(d[22]), "+f"(d[23]), "+f"(d[24]), "+f"(d[25]), "+f"(d[26]), "+f"(d[27]), "+f"(d[28]), "+f"(d[29]), "+f"(d[30]), "+f"(d[31]), "+f"(d[32]), "+f"(d[33]), "+f"(d[34]), "+f"(d[35]), "+f"(d[36]), "+f"(d[37]), "+f"(d[38]), "+f"(d[39]), "+f"(d[40]), "+f"(d[41]), "+f"(d[42]), "+f"(d[43]), "+f"(d[44]), "+f"(d[45]), "+f"(d[46]), "+f"(d[47]), "+f"(d[48]), "+f"(d[49]), "+f"(d[50]), "+f"(d[51]), "+f"(d[52]), "+f"(d[53]), "+f"(d[54]), "+f"(d[55]), "+f"(d[56]), "+f"(d[57]), "+f"(d[58]), "+f"(d[59]), "+f"(d[60]), "+f"(d[61]), "+f"(d[62]), "+f"(d[63]), "+f"(d[64]), "+f"(d[65]), "+f"(d[66]), "+f"(d[67]), "+f"(d[68]), "+f"(d[69]), "+f"(d[70]), "+f"(d[71]), "+f"(d[72]), "+f"(d[73]), "+f"(d[74]), "+f"(d[75]), "+f"(d[76]), "+f"(d[77]), "+f"(d[78]), "+f"(d[79])
    : "r"(a0), "r"(a1), "r"(a2), "r"(a3), "r"(dlo), "r"(acc), "n"(OFF >> 4), "n"(HI));
}

template <uint32_t OFF, uint32_t HI>
__device__ __forceinline__ void wgmma_ss_n24(float* d, uint32_t alo, uint32_t dlo) {
  asm volatile("{ .reg .b32 lo; .reg .b64 ds, da;\n"
    "add.u32 lo, %13, %14; mov.b64 ds, {lo, %15}; mov.b64 da, {%12, 16};\n"
    "wgmma.mma_async.sync.aligned.m64n24k16.f32.bf16.bf16 "
    "{%0, %1, %2, %3, %4, %5, %6, %7, %8, %9, %10, %11}, "
    "da, ds, 1, 1, 1, 0, 1; }"
    : "+f"(d[0]), "+f"(d[1]), "+f"(d[2]), "+f"(d[3]), "+f"(d[4]), "+f"(d[5]), "+f"(d[6]), "+f"(d[7]), "+f"(d[8]), "+f"(d[9]), "+f"(d[10]), "+f"(d[11])
    : "r"(alo), "r"(dlo), "n"(OFF >> 4), "n"(HI));
}

template <uint32_t OFF, uint32_t HI>
__device__ __forceinline__ void wgmma_ss_n64(float* d, uint32_t alo, uint32_t dlo) {
  asm volatile("{ .reg .b32 lo; .reg .b64 ds, da;\n"
    "add.u32 lo, %33, %34; mov.b64 ds, {lo, %35}; mov.b64 da, {%32, 16};\n"
    "wgmma.mma_async.sync.aligned.m64n64k16.f32.bf16.bf16 "
    "{%0, %1, %2, %3, %4, %5, %6, %7, %8, %9, %10, %11, %12, %13, %14, %15, %16, %17, %18, %19, %20, %21, %22, %23, %24, %25, %26, %27, %28, %29, %30, %31}, "
    "da, ds, 1, 1, 1, 0, 1; }"
    : "+f"(d[0]), "+f"(d[1]), "+f"(d[2]), "+f"(d[3]), "+f"(d[4]), "+f"(d[5]), "+f"(d[6]), "+f"(d[7]), "+f"(d[8]), "+f"(d[9]), "+f"(d[10]), "+f"(d[11]), "+f"(d[12]), "+f"(d[13]), "+f"(d[14]), "+f"(d[15]), "+f"(d[16]), "+f"(d[17]), "+f"(d[18]), "+f"(d[19]), "+f"(d[20]), "+f"(d[21]), "+f"(d[22]), "+f"(d[23]), "+f"(d[24]), "+f"(d[25]), "+f"(d[26]), "+f"(d[27]), "+f"(d[28]), "+f"(d[29]), "+f"(d[30]), "+f"(d[31])
    : "r"(alo), "r"(dlo), "n"(OFF >> 4), "n"(HI));
}

template <uint32_t OFF, uint32_t HI>
__device__ __forceinline__ void wgmma_ss_n128(float* d, uint32_t alo, uint32_t dlo) {
  asm volatile("{ .reg .b32 lo; .reg .b64 ds, da;\n"
    "add.u32 lo, %65, %66; mov.b64 ds, {lo, %67}; mov.b64 da, {%64, 16};\n"
    "wgmma.mma_async.sync.aligned.m64n128k16.f32.bf16.bf16 "
    "{%0, %1, %2, %3, %4, %5, %6, %7, %8, %9, %10, %11, %12, %13, %14, %15, %16, %17, %18, %19, %20, %21, %22, %23, %24, %25, %26, %27, %28, %29, %30, %31, %32, %33, %34, %35, %36, %37, %38, %39, %40, %41, %42, %43, %44, %45, %46, %47, %48, %49, %50, %51, %52, %53, %54, %55, %56, %57, %58, %59, %60, %61, %62, %63}, "
    "da, ds, 1, 1, 1, 0, 1; }"
    : "+f"(d[0]), "+f"(d[1]), "+f"(d[2]), "+f"(d[3]), "+f"(d[4]), "+f"(d[5]), "+f"(d[6]), "+f"(d[7]), "+f"(d[8]), "+f"(d[9]), "+f"(d[10]), "+f"(d[11]), "+f"(d[12]), "+f"(d[13]), "+f"(d[14]), "+f"(d[15]), "+f"(d[16]), "+f"(d[17]), "+f"(d[18]), "+f"(d[19]), "+f"(d[20]), "+f"(d[21]), "+f"(d[22]), "+f"(d[23]), "+f"(d[24]), "+f"(d[25]), "+f"(d[26]), "+f"(d[27]), "+f"(d[28]), "+f"(d[29]), "+f"(d[30]), "+f"(d[31]), "+f"(d[32]), "+f"(d[33]), "+f"(d[34]), "+f"(d[35]), "+f"(d[36]), "+f"(d[37]), "+f"(d[38]), "+f"(d[39]), "+f"(d[40]), "+f"(d[41]), "+f"(d[42]), "+f"(d[43]), "+f"(d[44]), "+f"(d[45]), "+f"(d[46]), "+f"(d[47]), "+f"(d[48]), "+f"(d[49]), "+f"(d[50]), "+f"(d[51]), "+f"(d[52]), "+f"(d[53]), "+f"(d[54]), "+f"(d[55]), "+f"(d[56]), "+f"(d[57]), "+f"(d[58]), "+f"(d[59]), "+f"(d[60]), "+f"(d[61]), "+f"(d[62]), "+f"(d[63])
    : "r"(alo), "r"(dlo), "n"(OFF >> 4), "n"(HI));
}

struct Params {
  CUtensorMap wqkv, wtail, wg, wu, wd, wo, out5, out4;
};

__device__ __forceinline__ void attn_group(uint32_t sb, int grp, int lane, int nvalid_base, int c, uint32_t* a2o) {
  const int row = grp * 8 + (lane >> 2), hh = lane & 3;
  const uint32_t a = sb + OFF_QKV + hh * 36 + row * QPITCH;
  float p[8];
#pragma unroll
  for (int j = 0; j < 8; j++) p[j] = 0.f;
#pragma unroll
  for (int w = 0; w < 9; w++) {
    const uint32_t qv = lds32(a + w * 4);
    const float q0 = blo(qv), q1 = bhi(qv);
#pragma unroll
    for (int j = 0; j < 8; j++) {
      const uint32_t v = lds32(a + 144 + w * 4 - j * 2 * QPITCH);
      p[j] = fmaf(q1, bhi(v), fmaf(q0, blo(v), p[j]));
    }
  }
  const int pos = nvalid_base + row;
  float mx = -3.0e38f;
#pragma unroll
  for (int j = 0; j < 8; j++) { p[j] = pos >= 2 * j ? p[j] * 0.23570226039551584f : -1e9f; mx = fmaxf(mx, p[j]); }
  float sum = 0.f;
#pragma unroll
  for (int j = 0; j < 8; j++) { p[j] = ex2((p[j] - mx) * 1.4426950408889634f); sum += p[j]; }
  const float inv = 1.0f / sum;
#pragma unroll
  for (int j = 0; j < 8; j++) p[j] *= inv;
  uint32_t* op = a2o + ((row >> 4) * 32 + (row & 7) * 4) * 4 + ((row >> 3) & 1);
  int pr = c * 36 + hh * 9;
  asm volatile("" : "+r"(pr));
#pragma unroll
  for (int w = 0; w < 9; w++, pr++) {
    float o0 = 0.f, o1 = 0.f;
#pragma unroll
    for (int j = 0; j < 8; j++) {
      const uint32_t v = lds32(a + 288 + w * 4 - j * 2 * QPITCH);
      o0 = fmaf(p[j], blo(v), o0); o1 = fmaf(p[j], bhi(v), o1);
    }
    op[((pr >> 3) << 10) + ((pr & 3) << 2) + ((pr >> 1) & 2)] = pack2(o0, o1);
  }
}

__global__ void __cluster_dims__(2, 1, 1) __launch_bounds__(384, 1)
fused_kernel(const __grid_constant__ Params P, const __nv_bfloat16* __restrict__ x, __nv_bfloat16* __restrict__ out,
             const __nv_bfloat16* __restrict__ wqkv, const __nv_bfloat16* __restrict__ wgate, const __nv_bfloat16* __restrict__ wup,
             const __nv_bfloat16* __restrict__ wdown, const __nv_bfloat16* __restrict__ wo) {
  extern __shared__ __align__(1024) unsigned char smem_raw[];
  const uint32_t sb = smem_u32(smem_raw);
  if (sb & 1023) __trap();
  const uint32_t bars = sb + OFF_BAR;
  const int warp = __shfl_sync(0xffffffff, threadIdx.x >> 5, 0), lane = threadIdx.x & 31;
  const int rank = blockIdx.x & 1, unit = blockIdx.x >> 1;
  const int g = unit >> 3, m = (unit & 7) * 2 + rank, s = g >> 1, c = g & 1;

  TMZERO();
  if (warp == 0) { TMG(0, 30); TM(0, 29); TM(0, 0); }
  if (warp == 8) {
    if (elect_one()) {
      prefetch_map(&P.wqkv);
      for (int i = 0; i < NSLOT; i++) { mbar_init(bars + BAR_FULL + 8 * i, 1); mbar_init(bars + BAR_EMPTY + 8 * i, 16); }
      mbar_init(bars + BAR_QKV, 8); mbar_init(bars + BAR_HDONE, 8); mbar_init(bars + BAR_DEPS, 1); mbar_init(bars + BAR_DEPH, 1);
      mbar_init(bars + BAR_DRAIN, 4); mbar_init(bars + BAR_DRAIN + 8, 4); mbar_init(bars + BAR_XDONE, 4); mbar_init(bars + BAR_ATTN, 1);
      asm volatile("fence.mbarrier_init.release.cluster;" ::: "memory");
      TM(2, 16);
    }
    __syncwarp();
  }
  asm volatile("barrier.cluster.arrive.relaxed.aligned;" ::: "memory");
  if (warp < 8) {
    if (warp >= 4) named_sync(5, 256);
    const unsigned char* src = reinterpret_cast<const unsigned char*>(x + (size_t)(m * 128 + warp * 16) * DM) + lane * 16;
    const uint32_t d0 = sb + (4 + warp) * SLOT + ((lane * 16) ^ ((lane >> 3) << 4));
#pragma unroll
    for (int i = 0; i < 36; i++) cp_async16(((i & 1) ? d0 ^ 64 : d0) + i * 512, src + i * 512);
    if (warp < 4) named_arrive(5, 256);
  }
  asm volatile("barrier.cluster.wait.aligned;" ::: "memory");
  if (warp < 8) TM(warp >> 2, 17);

  if (warp >= 8) {
    asm volatile("setmaxnreg.dec.sync.aligned.u32 40;");
    if (warp == 8) {
      if (elect_one()) {
        uint32_t epar = 0xf;
        for (int t = 0; t < 11; t++) {
          int col; const CUtensorMap* mp; uint32_t bytes = 16384;
          if (t == 0) { mp = &P.wqkv; col = rank * 576 + 72 * g; }
          else if (t == 1) { mp = &P.wqkv; col = 1152 + 72 * g; bytes = 8192 + 3072; }
          else { const int f = c ? 10 - t : t - 2; mp = rank ? &P.wu : &P.wg; col = 576 * g + 64 * f; }
          for (int kb = 0; kb < 9; kb++) {
            mbar_wait(bars + BAR_EMPTY + 8 * kb, (epar >> kb) & 1);
            epar ^= 1u << kb;
            if (t < 2 && !P2T) TM(2, 32 + t * 9 + kb);
            mbar_expect_tx(bars + BAR_FULL + 8 * kb, bytes);
            if (t == 1) {
              if (rank) tma_3d_mc(sb + kb * SLOT + 8192 + 2048, &P.wtail, 72 * g + 64, kb * 64, 2, bars + BAR_FULL + 8 * kb);
              else tma_2d_mc(sb + kb * SLOT, mp, col, kb * 64, bars + BAR_FULL + 8 * kb);
              tma_3d_mc(sb + kb * SLOT + 8192 + rank * 1024, &P.wtail, 72 * g + 64, kb * 64, rank, bars + BAR_FULL + 8 * kb);
            } else tma_2d_mc(sb + kb * SLOT + rank * 8192, mp, col, kb * 64, bars + BAR_FULL + 8 * kb);
            if (t == 0 && kb == 3) {
              prefetch_map(&P.wtail); prefetch_map(&P.wg); prefetch_map(&P.wu);
              prefetch_map(&P.wd); prefetch_map(&P.wo); prefetch_map(&P.out5); prefetch_map(&P.out4);
            }
          }
        }
        int slot = 0;
        for (int n = 0; n <= 40; n++) {
          mbar_wait(bars + BAR_EMPTY + 8 * slot, (epar >> slot) & 1);
          epar ^= 1u << slot;
          if (P2T && n < 18) TM(2, 32 + n);
          mbar_expect_tx(bars + BAR_FULL + 8 * slot, n < 40 ? 18432 : 9216);
          const int t = 2 * n + rank;
          if (t < NP2) {
            const int p = c ? 80 - t : t;
            const bool is_o = p >= 36 && p < 45;
            const int row = is_o ? 144 * s + 16 * (p - 36) : 1152 * s + 16 * (p < 36 ? p : p - 9);
            tma_3d_mc(sb + slot * SLOT + rank * 9216, is_o ? &P.wo : &P.wd, 0, row, 9 * c, bars + BAR_FULL + 8 * slot);
          }
          slot = slot == NSLOT - 1 ? 0 : slot + 1;
        }
      }
    } else {
      const int ht = threadIdx.x - 288, hw = warp - 9;
      if (ht == 0) sts32(bars + OFF_EPOCH, (atomicAdd(&g_ctr, 1u) >> 7) + 1u);
      if (ht >= 32 && ht < 48) { const int i = ht - 32; const __nv_bfloat16* b = (i >> 2) == 0 ? wgate : (i >> 2) == 1 ? wup : (i >> 2) == 2 ? wdown : wo;
        const int lim = (i >> 2) == 3 ? DM * DM : DM * FF; l2_prefetch_line(b + min((i & 3) * (1 << 20) + blockIdx.x * 64, lim - 64)); }
      mbar_wait(bars + BAR_XDONE, 0);
      {
        const uint4* xs = reinterpret_cast<const uint4*>(x + (size_t)(m * 128 + 32 * s) * DM + 288 * c);
        uint4* od = reinterpret_cast<uint4*>(out + (size_t)(m * 128 + 32 * s) * DM + 288 * c);
#pragma unroll 4
        for (int i = ht; i < 32 * 36; i += 96) { const int r = i / 36, ch = i - r * 36; od[r * 72 + ch] = __ldg(xs + r * 72 + ch); }
        asm volatile("fence.proxy.async.global;" ::: "memory");
      }
      named_sync(1, 96);
      const unsigned epoch = lds32(bars + OFF_EPOCH);
      mbar_wait(bars + BAR_QKV, 0);
      TM(2, 1);
      if (m < 15) {
        uint4* hd = g_halo + (m * 8 + g) * 252;
#pragma unroll 1
        for (int i = ht; i < 252; i += 96) { const int r = i / 18, ch = i - r * 18; hd[i] = lds128(sb + OFF_QKV + (114 + r) * QPITCH + 144 + ch * 16); }
        named_sync(1, 96);
        if (ht == 0) flag_set(&g_flag_halo[m * 8 + g], epoch);
      }
      uint32_t* a2o = reinterpret_cast<uint32_t*>(g_a2 + ((m * 4 + s) * NP2 + 36) * 256);
#pragma unroll 1
      for (int it = 0; it < 6; it++) {
        int grp = 2 + hw + 3 * it;
        if (it == 5) {
          grp = hw == 1 ? 16 : hw >> 1;
          if (m > 0) {
            if (lane == 0) flag_wait(&g_flag_halo[(m - 1) * 8 + g], epoch);
            __syncwarp();
          }
          const uint4* hs = g_halo + ((m - 1) * 8 + g) * 252;
#pragma unroll 1
          for (int i = ht; i < 252; i += 96) {
            const int r = i / 18, ch = i - r * 18;
            sts128(sb + OFF_HALO + r * QPITCH + 144 + ch * 16, m > 0 ? ldg_cg(hs + i) : lds128(sb + OFF_QKV + 144 + ch * 16));
          }
          named_sync(1, 96);
        }
        if (grp < 16) attn_group(sb, grp, lane, m * 128, c, a2o);
      }
      named_sync(1, 96);
      TM(2, 2);
      if (hw == 0) {
        if (lane == 0) mbar_arrive(bars + BAR_ATTN);
        if (lane == 0) flag_set(&g_flag_o[m * 8 + g], epoch);
        if (lane < 8) flag_wait(&g_flag_o[m * 8 + lane], epoch);
        __syncwarp();
        if (lane == 0) mbar_arrive(bars + BAR_DEPS);
        mbar_wait(bars + BAR_HDONE, 0);
        if (lane == 0) { flag_set(&g_flag_h[m * 8 + g], epoch); flag_wait(&g_flag_h[m * 8 + (g ^ 1)], epoch); mbar_arrive(bars + BAR_DEPH); }
        TM(2, 3);
        TMDUMP(2);
      }
    }
  } else {
    asm volatile("setmaxnreg.inc.sync.aligned.u32 232;");
    const int wg = warp >> 2, wi = warp & 3;
    TM(wg, 18);
    const uint32_t ebar = mapa(bars + BAR_EMPTY, lane & 1);
    uint32_t xa[144];
    float r0, r1;
    {
      const uint32_t xb = sb + (4 + warp) * SLOT + (lane & 15) * 1152;
      float ca[4][4], cb[4][4];
#pragma unroll
      for (int i = 0; i < 16; i++) { ca[i >> 2][i & 3] = 0.f; cb[i >> 2][i & 3] = 0.f; }
      asm volatile("cp.async.wait_all;" ::: "memory");
      __syncwarp();
      TM(wg, 19);
#pragma unroll
      for (int j = 0; j < 9 + LAGJ; j++) {
        if (j < 9) {
          const uint32_t sw = ((lane + j) & 7) << 4;
#pragma unroll
          for (int i = 0; i < 4; i++) {
            uint32_t* a = xa + 16 * j + 4 * i;
            asm volatile("ldmatrix.sync.aligned.m8n8.x4.shared.b16 {%0,%1,%2,%3}, [%4];"
                         : "=r"(a[0]), "=r"(a[1]), "=r"(a[2]), "=r"(a[3])
                         : "r"((xb | (((2 * i) << 4) ^ (lane & 16) ^ sw)) + j * 128) : "memory");
          }
        }
        if (j == 8) {
          if (wg == 0) { if (lane < 8) mbar_arrive_cl(ebar + 8 * (4 + (lane >> 1)), 2); else if (lane == 8) mbar_arrive(bars + BAR_XDONE); }
          else if (lane < 2) mbar_arrive_cl(ebar + 8 * 8, 2);
          TM(wg, 20);
        }
        if (j >= LAGJ) {
#pragma unroll
          for (int i = 0; i < 4; i++) {
            const uint32_t* a = xa + 16 * (j - LAGJ) + 4 * i;
            mma16816(ca[i], a[0], 0x3f803f80u, a[2], 0x3f803f80u, a[0], a[2]);
            mma16816(cb[i], a[1], 0x3f803f80u, a[3], 0x3f803f80u, a[1], a[3]);
          }
        }
      }
      if (wg == 1) named_arrive(6, 256);
#pragma unroll
      for (int i = 0; i < 4; i++) { ca[0][i] = (ca[0][i] + ca[2][i]); ca[1][i] = (ca[1][i] + ca[3][i]); cb[0][i] = (cb[0][i] + cb[2][i]); cb[1][i] = (cb[1][i] + cb[3][i]); }
      const int rr = lane >> 2, src = rr * 4 + (rr >> 1);
      const bool odd = rr & 1;
      const float q0 = __shfl_sync(0xffffffff, odd ? ca[0][1] + ca[1][1] : ca[0][0] + ca[1][0], src);
      const float q1 = __shfl_sync(0xffffffff, odd ? cb[0][1] + cb[1][1] : cb[0][0] + cb[1][0], src);
      const float s0 = __shfl_sync(0xffffffff, odd ? ca[0][3] + ca[1][3] : ca[0][2] + ca[1][2], src);
      const float s1 = __shfl_sync(0xffffffff, odd ? cb[0][3] + cb[1][3] : cb[0][2] + cb[1][2], src);
      TM(wg, 1);
      const float m0 = s0 * (1.0f / DM), m1 = s1 * (1.0f / DM);
      r0 = rsqrtf(fmaxf(q0 * (1.0f / DM) - m0 * m0, 0.f) + 1e-5f);
      r1 = rsqrtf(fmaxf(q1 * (1.0f / DM) - m1 * m1, 0.f) + 1e-5f);
      const uint32_t mm0 = pack2(m0, m0), mm1 = pack2(m1, m1);
#pragma unroll
      for (int i = 0; i < 144; i += 2) { xa[i] = bsub2(xa[i], mm0); xa[i + 1] = bsub2(xa[i + 1], mm1); }
      const uint32_t ax = sb + OFF_AX + wg * 2048 + wi * 512 + lane * 4;
      sts32(ax, xa[140]); sts32(ax + 256, xa[141]); sts32(ax + 128, xa[142]); sts32(ax + 384, xa[143]);
    }
    const uint32_t dax = desc_lo(sb + OFF_AX + wg * 2048, 128);
    TM(wg, 2);
    const uint32_t d128 = desc_lo(sb, 8192);
    const uint32_t qrow = sb + OFF_QKV + (wg * 64 + wi * 16 + (lane >> 2)) * QPITCH + (lane & 3) * 4;
#define P1_MAIN(PARITY, MMA, EXTRA, TMB)                                                        \
    static_for<0, 9>([&](auto KB) {                                                 \
      constexpr int kb = decltype(KB)::value;                                                        \
      if constexpr (kb == (TMB == 32 ? PP_KB0 : TMB == 41 ? PP_KB1 : PP_KB)) { if (wg == 1) named_sync(4, 256); }                \
      if constexpr (kb == HOLD_KB && TMB == 32) { if (wg == 0) named_sync(6, 256); }               \
      mbar_wait(bars + BAR_FULL + 8 * kb, (PARITY));                                \
      if (TMB && !P2T) TM(wg, TMB + kb);                                                    \
      wg_fence();                                                                   \
      static_for<0, 4>([&](auto I) { constexpr int i = decltype(I)::value; const uint32_t* a = xa + 16 * kb + 4 * i;       \
        if constexpr (kb == 8 && i == 3) { MMA##_SS; } else { MMA; } });            \
      wg_commit();                                                                  \
      if constexpr (kb == 8) { if (wg == 0) named_arrive(4, 256); }                 \
      EXTRA;                                                                        \
      if constexpr (kb >= WDEPTH) { wg_wait<WDEPTH>(); if (lane < 2) mbar_arrive_cl(ebar + 8 * (kb - WDEPTH), 1); } \
    });                                                                             \
    if constexpr (WDEPTH == 2) { wg_wait<1>(); if (lane < 2) mbar_arrive_cl(ebar + 8 * 7, 1); } \
    wg_wait<0>();                                                                   \
    if (lane < 2) mbar_arrive_cl(ebar + 8 * 8, 1);
#define MMA128 (wgmma_n128<kb * SLOT + i * 2048, HI128>(acc, a[0], a[1], a[2], a[3], d128, kb + i))
#define MMA128_SS (wgmma_ss_n128<kb * SLOT + i * 2048, HI128>(acc, dax, d128))
    {
    float acc[64];
    P1_MAIN(0, MMA128, if constexpr (kb == 2) { asm volatile("fence.proxy.async.shared::cta;" ::: "memory"); named_sync(2 + wg, 128); }, 32)
    keep<64>(acc);
#pragma unroll
    for (int j = 0; j < 16; j++) {
      const uint32_t a = qrow + (j >> 3) * 144 + (j & 7) * 16;
      sts32(a, pack2(acc[4 * j] * r0, acc[4 * j + 1] * r0));
      sts32(a + 8 * QPITCH, pack2(acc[4 * j + 2] * r1, acc[4 * j + 3] * r1));
    }
    }
    TM(wg, 3);
    {
      const uint32_t dtail = desc_lo(sb + 8192, 128);
      float av[32], at[12];
#define MMAQ2 (wgmma_n64<kb * SLOT + i * 2048, HI128>(av, a[0], a[1], a[2], a[3], d128, kb + i), \
               wgmma_n24<kb * SLOT + i * 256, HI0>(at, a[0], a[1], a[2], a[3], dtail, kb + i))
#define MMAQ2_SS (wgmma_ss_n64<kb * SLOT + i * 2048, HI128>(av, dax, d128), wgmma_ss_n24<kb * SLOT + i * 256, HI0>(at, dax, dtail))
      P1_MAIN(1, MMAQ2, , 41)
      keep<32>(av); keep<12>(at);
#pragma unroll
      for (int j = 0; j < 11; j++) {
        const uint32_t a = qrow + (j < 8 ? 288 + j * 16 : (j - 8) * 144 + 128);
        const float* d = j < 8 ? av + 4 * j : at + 4 * (j - 8);
        sts32(a, pack2(d[0] * r0, d[1] * r0));
        sts32(a + 8 * QPITCH, pack2(d[2] * r1, d[3] * r1));
      }
      __syncwarp();
      if (lane == 0) mbar_arrive(bars + BAR_QKV);
    }
    TM(wg, 4);
    uint4* const a2u = g_a2 + (m * 4 + s) * NP2 * 256;
    const float ke0 = r0 * -1.4426950408889634f, ke1 = r1 * -1.4426950408889634f, sd0 = 1.0f / r0, sd1 = 1.0f / r1;
#pragma unroll 1
    for (int t = 2; t < 11; t++) {
      float acc[64];
      P1_MAIN(t & 1, MMA128, , 0)
      keep<64>(acc);
      if (t == 10) {
        mbar_wait(bars + BAR_ATTN, 0);
        const uint32_t tn = tid_now(), ast0 = sb + OFF_AST + warp * AST_WARP + (tn & 31) * 16;
        const uint4* src = a2u + tn + (c ? 80 * 256 : 0);
        const int ds = c ? -256 : 256;
#pragma unroll
        for (int u = 0; u < 12; u++) {
          cp_async16(ast0 + u * 512, src);
          src += ds;
          if (u & 1) asm volatile("cp.async.commit_group;" ::: "memory");
        }
      }
      uint4* hp = a2u + (c ? 45 + 4 * (10 - t) : 4 * (t - 2)) * 256 + tid_now();
#pragma unroll
      for (int i = 0; i < 4; i++) {
        uint4 v;
        v.x = pack2(glu(acc[8 * i], acc[32 + 8 * i], ke0, sd0), glu(acc[8 * i + 1], acc[32 + 8 * i + 1], ke0, sd0));
        v.y = pack2(glu(acc[8 * i + 2], acc[32 + 8 * i + 2], ke1, sd1), glu(acc[8 * i + 3], acc[32 + 8 * i + 3], ke1, sd1));
        v.z = pack2(glu(acc[8 * i + 4], acc[32 + 8 * i + 4], ke0, sd0), glu(acc[8 * i + 5], acc[32 + 8 * i + 5], ke0, sd0));
        v.w = pack2(glu(acc[8 * i + 6], acc[32 + 8 * i + 6], ke1, sd1), glu(acc[8 * i + 7], acc[32 + 8 * i + 7], ke1, sd1));
        hp[i * 256] = v;
      }
      TM(wg, 3 + t);
    }
    __syncwarp();
    if (lane == 0) mbar_arrive(bars + BAR_HDONE);

    float oa[80], ob[64];
    uint4 af[4];
    const int dstep = c ? -256 : 256;
    const uint4* ap = a2u + (c ? 68 : 12) * 256 + tid_now();
    const uint32_t ast = sb + OFF_AST + warp * AST_WARP + (tid_now() & 31) * 16;
    const uint32_t d64 = desc_lo(sb, 1024);
    int slot = 0, par = 1, prev = 0, rst = 0, wst = 6;
    asm volatile("cp.async.wait_group 5;" ::: "memory");
    af[0] = lds128(ast); af[1] = lds128(ast + 512);
#pragma unroll 1
    for (int it = 0; it < 20; it++) {
#pragma unroll
      for (int u = 0; u < 2; u++) {
        const int n = it * 2 + u;
        mbar_wait(bars + BAR_FULL + 8 * slot, par);
        if (P2T && n < 18) TM(wg, 32 + n);
        const uint32_t d = d64 + slot * (SLOT >> 4);
        wg_fence();
        wgmma_n160<0, HI64>(oa, af[2 * u].x, af[2 * u].y, af[2 * u].z, af[2 * u].w, d, n);
        wgmma_n128<5120, HI64>(ob, af[2 * u].x, af[2 * u].y, af[2 * u].z, af[2 * u].w, d, n);
        wgmma_n160<9216, HI64>(oa, af[2 * u + 1].x, af[2 * u + 1].y, af[2 * u + 1].z, af[2 * u + 1].w, d, 1);
        wgmma_n128<9216 + 5120, HI64>(ob, af[2 * u + 1].x, af[2 * u + 1].y, af[2 * u + 1].z, af[2 * u + 1].w, d, 1);
        wg_commit();
        if (u == 0 && it == 6) mbar_wait(bars + BAR_DEPS, 0);
        if (u == 0 && it == 8) { mbar_wait(bars + BAR_DEPH, 0); TM(wg, 22); }
        if (n <= 34) cp_async16(ast + wst * 1024, ap);
        if (n <= 33) cp_async16(ast + wst * 1024 + 512, ap + dstep);
        asm volatile("cp.async.commit_group;\n cp.async.wait_group 5;" ::: "memory");
        ap += 2 * dstep;
        wst = rst;
        rst = rst == 6 ? 0 : rst + 1;
        wg_wait<1>();
        if (n > 0 && n <= 32) { if (lane < 2) mbar_arrive_cl(ebar + 8 * prev, 1); }
        if (n == 34) { if (lane == 0) mbar_arrive(bars + BAR_DRAIN + 8 * (wg ^ 1)); }
        af[2 * (u ^ 1)] = lds128(ast + rst * 1024);
        af[2 * (u ^ 1) + 1] = lds128(ast + rst * 1024 + 512);
        prev = slot;
        if (++slot == NSLOT) { slot = 0; par ^= 1; }
      }
    }
    {
      mbar_wait(bars + BAR_FULL + 8 * slot, par);
      const uint32_t d = d64 + slot * (SLOT >> 4);
      wg_fence();
      wgmma_n160<0, HI64>(oa, af[0].x, af[0].y, af[0].z, af[0].w, d, 1);
      wgmma_n128<5120, HI64>(ob, af[0].x, af[0].y, af[0].z, af[0].w, d, 1);
      wg_commit();
      wg_wait<0>();
      keep<80>(oa); keep<64>(ob);
    }
    TM(wg, 14);
    {
      const int row = lane & 15;
      const uint32_t sw = (row >> 1) & 3, hi = lane >> 4;
      const uint32_t sta = sb + OFF_AST + warp * AST_WARP, stb = sb + (5 + wg) * SLOT + wi * 4096;
      __syncwarp();
#pragma unroll
      for (int j = 0; j < 18; j++) {
        if (j == 10) {
          asm volatile("fence.proxy.async.shared::cta;" ::: "memory");
          __syncwarp();
          if (lane == 0) tma_red_3d(&P.out5, 0, m * 128 + warp * 16, 9 * c, sta);
          mbar_wait(bars + BAR_DRAIN + 8 * wg, 0);
        }
        const float* d = j < 10 ? oa + 8 * j : ob + 8 * (j - 10);
        const uint32_t addr = (j < 10 ? sta + (j >> 1) * 1024 : stb + ((j - 10) >> 1) * 1024) + row * 64 + (((((j & 1) << 1) | hi) ^ sw) << 4);
        asm volatile("stmatrix.sync.aligned.m8n8.x4.shared.b16 [%0], {%1,%2,%3,%4};"
                     ::"r"(addr), "r"(pack2(d[0], d[1])), "r"(pack2(d[2], d[3])), "r"(pack2(d[4], d[5])), "r"(pack2(d[6], d[7])) : "memory");
      }
      asm volatile("fence.proxy.async.shared::cta;" ::: "memory");
      __syncwarp();
      if (lane == 0) {
        tma_red_3d(&P.out4, 0, m * 128 + warp * 16, 9 * c + 5, stb);
        asm volatile("cp.async.bulk.commit_group;\n cp.async.bulk.wait_group.read 0;" ::: "memory");
      }
    }
    TM(wg, 15);
    TMG(wg, 31);
    TMDUMP(wg);
  }
}

typedef CUresult (*EncodeFn)(CUtensorMap*, CUtensorMapDataType, cuuint32_t, void*, const cuuint64_t*, const cuuint64_t*,
                             const cuuint32_t*, const cuuint32_t*, CUtensorMapInterleave, CUtensorMapSwizzle,
                             CUtensorMapL2promotion, CUtensorMapFloatOOBfill);

void encode(EncodeFn fn, CUtensorMap* mp, const void* base, int rank, uint64_t d0, uint64_t d1, uint64_t d2, uint64_t s1,
            uint64_t s2, uint32_t b0, uint32_t b1, uint32_t b2, CUtensorMapSwizzle swz) {
  cuuint64_t dims[3] = {d0, d1, d2}, strides[2] = {s1, s2};
  cuuint32_t box[3] = {b0, b1, b2}, es[3] = {1, 1, 1};
  fn(mp, CU_TENSOR_MAP_DATA_TYPE_BFLOAT16, rank, const_cast<void*>(base), dims, strides, box, es,
     CU_TENSOR_MAP_INTERLEAVE_NONE, swz, CU_TENSOR_MAP_L2_PROMOTION_L2_256B, CU_TENSOR_MAP_FLOAT_OOB_FILL_NONE);
}

}

extern "C" void kernel_launch(void* const* d_in, const int* in_sizes, int n_in, void* d_out, int out_size) {
  (void)in_sizes; (void)n_in; (void)out_size;
  const void *x = d_in[0], *wqkv = d_in[1], *wo = d_in[2], *wgate = d_in[4], *wup = d_in[5], *wdown = d_in[6];
  EncodeFn fn = nullptr;
  cudaDriverEntryPointQueryResult qr;
  cudaGetDriverEntryPoint("cuTensorMapEncodeTiled", (void**)&fn, cudaEnableDefault, &qr);
  Params P;
  encode(fn, &P.wqkv, wqkv, 2, 3 * DM, DM, 1, 3 * DM * 2, 0, 64, 64, 1, CU_TENSOR_MAP_SWIZZLE_128B);
  encode(fn, &P.wtail, wqkv, 3, DM, DM, 3, 3 * DM * 2, DM * 2, 8, 64, 1, CU_TENSOR_MAP_SWIZZLE_NONE);
  encode(fn, &P.wg, wgate, 2, FF, DM, 1, FF * 2, 0, 64, 64, 1, CU_TENSOR_MAP_SWIZZLE_128B);
  encode(fn, &P.wu, wup, 2, FF, DM, 1, FF * 2, 0, 64, 64, 1, CU_TENSOR_MAP_SWIZZLE_128B);
  encode(fn, &P.wd, wdown, 3, 32, FF, 18, DM * 2, 64, 32, 16, 9, CU_TENSOR_MAP_SWIZZLE_64B);
  encode(fn, &P.wo, wo, 3, 32, DM, 18, DM * 2, 64, 32, 16, 9, CU_TENSOR_MAP_SWIZZLE_64B);
  encode(fn, &P.out5, d_out, 3, 32, SEQ, 18, DM * 2, 64, 32, 16, 5, CU_TENSOR_MAP_SWIZZLE_64B);
  encode(fn, &P.out4, d_out, 3, 32, SEQ, 18, DM * 2, 64, 32, 16, 4, CU_TENSOR_MAP_SWIZZLE_64B);
  cudaFuncSetAttribute(fused_kernel, cudaFuncAttributeMaxDynamicSharedMemorySize, SMEM_BYTES);
  fused_kernel<<<128, 384, SMEM_BYTES, cudaStreamPerThread>>>(P, (const __nv_bfloat16*)x, (__nv_bfloat16*)d_out, (const __nv_bfloat16*)wqkv,
      (const __nv_bfloat16*)wgate, (const __nv_bfloat16*)wup, (const __nv_bfloat16*)wdown, (const __nv_bfloat16*)wo);
}
```

```cpp
#include <cuda_runtime.h>
#include <cuda.h>
#include <cuda_bf16.h>
#include <stdint.h>
#include <type_traits>

namespace {

constexpr int SEQ = 2048, DM = 576, FF = 4608;
constexpr int SLOT = 18432, NSLOT = 9;
constexpr int QPITCH = 432;
constexpr int OFF_HALO = 9 * SLOT;
constexpr int OFF_QKV = OFF_HALO + 14 * QPITCH;
constexpr int OFF_AST = 9 * SLOT, AST_WARP = 7680;
constexpr int OFF_AX = 12 * SLOT + 6144;
constexpr int OFF_BAR = OFF_AX + 4096;
constexpr int BAR_FULL = 0, BAR_EMPTY = 96;
constexpr int BAR_X0 = 288, BAR_X0F = 296, BAR_X1E = 304, BAR_X1 = 312;
constexpr int BAR_XDONE = 192;
constexpr int BAR_STAT = 224;
constexpr int BAR_QKV0 = 240, BAR_QKV1 = 216;
constexpr int BAR_H5 = 88, BAR_HDONE = 248;
constexpr int BAR_AXW = 256;
constexpr int BAR_STG = 208;
constexpr int BAR_DEPS = 168, BAR_DEPH = 176, BAR_DEPX = 200;
constexpr int BAR_FL = 320;
constexpr int OFF_EPOCH = 280;
constexpr int SMEM_BYTES = OFF_BAR + 400;
static_assert(SMEM_BYTES <= 232448 && OFF_QKV + 128 * QPITCH <= OFF_AX, "smem");
constexpr int NP2 = 83;
constexpr unsigned SPIN_LIMIT = 1u << 22;
constexpr int SPARE_DELAY = 4000;
constexpr int FS = 32;

struct Scratch {
  uint4 a2[16 * 4 * NP2 * 256];
  uint4 halo[16 * 8 * 14 * 18];
  uint2 stat[SEQ];
  unsigned flag_halo[128 * FS], flag_o[144 * FS], flag_h[128 * FS];
  unsigned ctr[132 * FS];
};
__device__ Scratch g_s;

__device__ __forceinline__ uint32_t smem_u32(const void* p) { return (uint32_t)__cvta_generic_to_shared(p); }
__device__ __forceinline__ void mbar_init(uint32_t bar, uint32_t cnt) {
  asm volatile("mbarrier.init.shared::cta.b64 [%0], %1;" ::"r"(bar), "r"(cnt) : "memory");
}
__device__ __forceinline__ void mbar_expect_tx(uint32_t bar, uint32_t bytes) {
  asm volatile("mbarrier.arrive.expect_tx.shared::cta.b64 _, [%0], %1;" ::"r"(bar), "r"(bytes) : "memory");
}
__device__ __forceinline__ void mbar_arrive(uint32_t bar) {
  asm volatile("mbarrier.arrive.shared::cta.b64 _, [%0];" ::"r"(bar) : "memory");
}
__device__ __forceinline__ void mbar_arrive_cl(uint32_t bar, uint32_t cnt) {
  asm volatile("mbarrier.arrive.shared::cluster.b64 _, [%0], %1;" ::"r"(bar), "r"(cnt) : "memory");
}
__device__ __forceinline__ void mbar_arrive_cl1(uint32_t bar) {
  asm volatile("mbarrier.arrive.shared::cluster.b64 _, [%0];" ::"r"(bar) : "memory");
}
__device__ __forceinline__ uint32_t mapa(uint32_t addr, uint32_t cta) {
  uint32_t r; asm("mapa.shared::cluster.u32 %0, %1, %2;" : "=r"(r) : "r"(addr), "r"(cta)); return r;
}
__device__ __forceinline__ void mbar_wait(uint32_t bar, uint32_t parity) {
  asm volatile(
      "{\n"
      ".reg .pred p;\n"
      ".reg .u32 n;\n"
      "mov.u32 n, 0;\n"
      "WAIT_LOOP:\n"
      "mbarrier.try_wait.parity.shared::cta.b64 p, [%0], %1;\n"
      "@p bra WAIT_DONE;\n"
      "add.u32 n, n, 1;\n"
      "setp.lt.u32 p, n, %2;\n"
      "@p bra WAIT_LOOP;\n"
      "trap;\n"
      "WAIT_DONE:\n"
      "}\n" ::"r"(bar), "r"(parity), "n"(1u << 22) : "memory");
}
__device__ __forceinline__ void mbar_spin(uint32_t bar, uint32_t parity) {
  asm volatile("{ .reg .pred p; WAIT_LOOP: mbarrier.try_wait.parity.shared::cta.b64 p, [%0], %1; @!p bra WAIT_LOOP; }" ::"r"(bar), "r"(parity) : "memory");
}
__device__ __forceinline__ uint32_t mbar_test(uint32_t bar, uint32_t parity) {
  uint32_t ok;
  asm volatile("{ .reg .pred p; mbarrier.test_wait.parity.shared::cta.b64 p, [%1], %2; selp.u32 %0, 1, 0, p; }" : "=r"(ok) : "r"(bar), "r"(parity) : "memory");
  return ok;
}
__device__ __forceinline__ bool elect_one() {
  uint32_t p;
  asm volatile("{ .reg .pred q; elect.sync _|q, 0xffffffff; selp.u32 %0, 1, 0, q; }" : "=r"(p));
  return p;
}
__device__ __forceinline__ void tma_2d_mc(uint32_t dst, const CUtensorMap* m, int c0, int c1, uint32_t bar, uint64_t pol) {
  asm volatile("cp.async.bulk.tensor.2d.shared::cluster.global.mbarrier::complete_tx::bytes.multicast::cluster.L2::cache_hint"
               " [%0], [%1, {%3, %4}], [%2], %5, %6;"
               ::"r"(dst), "l"(m), "r"(bar), "r"(c0), "r"(c1), "h"((uint16_t)3), "l"(pol) : "memory");
}
__device__ __forceinline__ void tma_3d_mc(uint32_t dst, const CUtensorMap* m, int c0, int c1, int c2, uint32_t bar, uint64_t pol) {
  asm volatile("cp.async.bulk.tensor.3d.shared::cluster.global.mbarrier::complete_tx::bytes.multicast::cluster.L2::cache_hint"
               " [%0], [%1, {%3, %4, %5}], [%2], %6, %7;"
               ::"r"(dst), "l"(m), "r"(bar), "r"(c0), "r"(c1), "r"(c2), "h"((uint16_t)3), "l"(pol) : "memory");
}
__device__ __forceinline__ void tma_red_2d(const CUtensorMap* m, int c0, int c1, uint32_t src) {
  asm volatile("cp.reduce.async.bulk.tensor.2d.global.shared::cta.add.bulk_group [%0, {%2, %3}], [%1];"
               ::"l"(m), "r"(src), "r"(c0), "r"(c1) : "memory");
}
__device__ __forceinline__ void prefetch_map(const CUtensorMap* m) {
  asm volatile("prefetch.tensormap [%0];" ::"l"(m) : "memory");
}
__device__ __forceinline__ void cp_async16(uint32_t dst, const void* src) {
  asm volatile("cp.async.cg.shared.global [%0], [%1], 16;" ::"r"(dst), "l"(src) : "memory");
}
__device__ __forceinline__ void wg_fence() { asm volatile("wgmma.fence.sync.aligned;" ::: "memory"); }
__device__ __forceinline__ void wg_commit() { asm volatile("wgmma.commit_group.sync.aligned;" ::: "memory"); }
template <int N> __device__ __forceinline__ void wg_wait() { asm volatile("wgmma.wait_group.sync.aligned %0;" ::"n"(N) : "memory"); }
template <int N> __device__ __forceinline__ void keep(float* d) {
#pragma unroll
  for (int i = 0; i < N; i++) asm volatile("" : "+f"(d[i])::"memory");
}
template <int N> __device__ __forceinline__ void rename(float* d, const float* s) {
#pragma unroll
  for (int i = 0; i < N; i++) asm volatile("mov.b32 %0, %1;" : "=f"(d[i]) : "f"(s[i]) : "memory");
}
__device__ __forceinline__ void named_sync(int id, int n) { asm volatile("bar.sync %0, %1;" ::"r"(id), "r"(n) : "memory"); }
__device__ __forceinline__ void named_arrive(int id, int n) { asm volatile("bar.arrive %0, %1;" ::"r"(id), "r"(n) : "memory"); }
__device__ __forceinline__ uint32_t pack2(float lo, float hi) {
  uint32_t r; asm("cvt.rn.bf16x2.f32 %0, %1, %2;" : "=r"(r) : "f"(hi), "f"(lo)); return r;
}
__device__ __forceinline__ float blo(uint32_t v) { return __uint_as_float(v << 16); }
__device__ __forceinline__ float bhi(uint32_t v) { return __uint_as_float(v & 0xffff0000u); }
__device__ __forceinline__ uint32_t lds32(uint32_t a) { uint32_t v; asm volatile("ld.shared.u32 %0, [%1];" : "=r"(v) : "r"(a)); return v; }
__device__ __forceinline__ void sts32(uint32_t a, uint32_t v) { asm volatile("st.shared.u32 [%0], %1;" ::"r"(a), "r"(v) : "memory"); }
__device__ __forceinline__ uint4 lds128(uint32_t a) {
  uint4 v; asm volatile("ld.shared.v4.u32 {%0,%1,%2,%3}, [%4];" : "=r"(v.x), "=r"(v.y), "=r"(v.z), "=r"(v.w) : "r"(a)); return v;
}
__device__ __forceinline__ void sts128(uint32_t a, uint4 v) {
  asm volatile("st.shared.v4.u32 [%0], {%1,%2,%3,%4};" ::"r"(a), "r"(v.x), "r"(v.y), "r"(v.z), "r"(v.w) : "memory");
}
__device__ __forceinline__ uint4 ldg_cg(const uint4* p) {
  uint4 v; asm volatile("ld.global.cg.v4.u32 {%0,%1,%2,%3}, [%4];" : "=r"(v.x), "=r"(v.y), "=r"(v.z), "=r"(v.w) : "l"(p) : "memory"); return v;
}
__device__ __forceinline__ void flag_set(unsigned* f, unsigned v) {
  asm volatile("fence.acq_rel.gpu;\n st.relaxed.gpu.global.u32 [%0], %1;" ::"l"(f), "r"(v) : "memory");
}
__device__ __forceinline__ void flag_wait(const unsigned* f, unsigned v) {
  unsigned cur, n = 0;
  do {
    asm volatile("ld.acquire.gpu.global.u32 %0, [%1];" : "=r"(cur) : "l"(f) : "memory");
    if (++n > SPIN_LIMIT) __trap();
    if (cur != v) __nanosleep(200);
  } while (cur != v);
}
__device__ __forceinline__ bool computed(float v) { return __float_as_uint(v) != 0x7fc17fc1u; }
__device__ __forceinline__ uint32_t tid_now() { uint32_t t; asm volatile("mov.u32 %0, %%tid.x;" : "=r"(t)); return t; }
__device__ __forceinline__ float ex2(float x) { float r; asm("ex2.approx.ftz.f32 %0, %1;" : "=f"(r) : "f"(x)); return r; }
__device__ __forceinline__ float rcp(float x) { float r; asm("rcp.approx.ftz.f32 %0, %1;" : "=f"(r) : "f"(x)); return r; }
__device__ __forceinline__ void stsm_scaled(uint32_t a, const float* d, float r0 = 1.f, float r1 = 1.f) {
  asm volatile("stmatrix.sync.aligned.m8n8.x4.shared.b16 [%0], {%1,%2,%3,%4};" ::"r"(a), "r"(pack2(d[0] * r0, d[1] * r0)),
               "r"(pack2(d[2] * r1, d[3] * r1)), "r"(pack2(d[4] * r0, d[5] * r0)), "r"(pack2(d[6] * r1, d[7] * r1)) : "memory");
}
__device__ __forceinline__ float glu(float g, float u, float hr = 1.f) {
  float t; asm("tanh.approx.f32 %0, %1;" : "=f"(t) : "f"(g * hr));
  const float v = u * hr;
  return fmaf(t, v, v);
}
__device__ __forceinline__ void mma16816(float* c, uint32_t a0, uint32_t a1, uint32_t a2, uint32_t a3, uint32_t b0, uint32_t b1) {
  asm volatile("mma.sync.aligned.m16n8k16.row.col.f32.bf16.bf16.f32 {%0,%1,%2,%3}, {%4,%5,%6,%7}, {%8,%9}, {%0,%1,%2,%3};"
      : "+f"(c[0]), "+f"(c[1]), "+f"(c[2]), "+f"(c[3]) : "r"(a0), "r"(a1), "r"(a2), "r"(a3), "r"(b0), "r"(b1));
}
__device__ __forceinline__ void mma1688(float* c, uint32_t a0, uint32_t a1, uint32_t b0) {
  asm volatile("mma.sync.aligned.m16n8k8.row.col.f32.bf16.bf16.f32 {%0,%1,%2,%3}, {%4,%5}, {%6}, {%0,%1,%2,%3};"
      : "+f"(c[0]), "+f"(c[1]), "+f"(c[2]), "+f"(c[3]) : "r"(a0), "r"(a1), "r"(b0));
}
template <int N> __device__ __forceinline__ void center(uint32_t* a, uint32_t m0, uint32_t m1) {
#pragma unroll
  for (int i = 0; i < N; i++) asm volatile("sub.rn.bf16x2 %0, %0, %1;" : "+r"(a[i]) : "r"((i & 1) ? m1 : m0));
}
template <int N> __device__ __forceinline__ void scale(uint32_t* a, uint32_t m0, uint32_t m1) {
#pragma unroll
  for (int i = 0; i < N; i++) asm volatile("mul.rn.bf16x2 %0, %0, %1;" : "+r"(a[i]) : "r"((i & 1) ? m1 : m0));
}

__device__ __forceinline__ uint32_t desc_lo(uint32_t addr, uint32_t lbo) { return ((addr >> 4) & 0x3fff) | ((lbo >> 4) << 16); }
constexpr uint32_t HI128 = (1024 >> 4) | (1u << 30), HI64 = (512 >> 4) | (2u << 30), HI0 = (1024 >> 4);
template <int I, int N, class F> __device__ __forceinline__ void static_for(F&& f) {
  if constexpr (I < N) { f(std::integral_constant<int, I>{}); static_for<I + 1, N>(f); }
}

template <uint32_t HI> __device__ __forceinline__ uint64_t desc64(uint32_t lo) {
  uint64_t d; asm("mov.b64 %0, {%1, %2};" : "=l"(d) : "r"(lo), "n"(HI)); return d;
}
template <uint32_t HI> __device__ __forceinline__ uint64_t desc64(uint64_t d) { return d; }
template <uint32_t OFF, uint32_t HI, class D>
__device__ __forceinline__ void wgmma_n24(float* d, uint32_t a0, uint32_t a1, uint32_t a2, uint32_t a3, D dlo, int acc) {
  asm volatile("{ .reg .pred p; .reg .b64 ds; setp.ne.b32 p, %17, 0;\n"
    "add.u64 ds, %16, %18;\n"
    "wgmma.mma_async.sync.aligned.m64n24k16.f32.bf16.bf16 "
    "{%0, %1, %2, %3, %4, %5, %6, %7, %8, %9, %10, %11}, "
    "{%12, %13, %14, %15}, ds, p, 1, 1, 1; }"
    : "+f"(d[0]), "+f"(d[1]), "+f"(d[2]), "+f"(d[3]), "+f"(d[4]), "+f"(d[5]), "+f"(d[6]), "+f"(d[7]), "+f"(d[8]), "+f"(d[9]), "+f"(d[10]), "+f"(d[11])
    : "r"(a0), "r"(a1), "r"(a2), "r"(a3), "l"(desc64<HI>(dlo)), "r"(acc), "n"(OFF >> 4));
}

template <uint32_t OFF, uint32_t HI, class D>
__device__ __forceinline__ void wgmma_n32(float* d, uint32_t a0, uint32_t a1, uint32_t a2, uint32_t a3, D dlo, int acc) {
  asm volatile("{ .reg .pred p; .reg .b64 ds; setp.ne.b32 p, %21, 0;\n"
    "add.u64 ds, %20, %22;\n"
    "wgmma.mma_async.sync.aligned.m64n32k16.f32.bf16.bf16 "
    "{%0, %1, %2, %3, %4, %5, %6, %7, %8, %9, %10, %11, %12, %13, %14, %15}, "
    "{%16, %17, %18, %19}, ds, p, 1, 1, 1; }"
    : "+f"(d[0]), "+f"(d[1]), "+f"(d[2]), "+f"(d[3]), "+f"(d[4]), "+f"(d[5]), "+f"(d[6]), "+f"(d[7]), "+f"(d[8]), "+f"(d[9]), "+f"(d[10]), "+f"(d[11]), "+f"(d[12]), "+f"(d[13]), "+f"(d[14]), "+f"(d[15])
    : "r"(a0), "r"(a1), "r"(a2), "r"(a3), "l"(desc64<HI>(dlo)), "r"(acc), "n"(OFF >> 4));
}

template <uint32_t OFF, uint32_t HI, class D>
__device__ __forceinline__ void wgmma_n48(float* d, uint32_t a0, uint32_t a1, uint32_t a2, uint32_t a3, D dlo, int acc) {
  asm volatile("{ .reg .pred p; .reg .b64 ds; setp.ne.b32 p, %29, 0;\n"
    "add.u64 ds, %28, %30;\n"
    "wgmma.mma_async.sync.aligned.m64n48k16.f32.bf16.bf16 "
    "{%0, %1, %2, %3, %4, %5, %6, %7, %8, %9, %10, %11, %12, %13, %14, %15, %16, %17, %18, %19, %20, %21, %22, %23}, "
    "{%24, %25, %26, %27}, ds, p, 1, 1, 1; }"
    : "+f"(d[0]), "+f"(d[1]), "+f"(d[2]), "+f"(d[3]), "+f"(d[4]), "+f"(d[5]), "+f"(d[6]), "+f"(d[7]), "+f"(d[8]), "+f"(d[9]), "+f"(d[10]), "+f"(d[11]), "+f"(d[12]), "+f"(d[13]), "+f"(d[14]), "+f"(d[15]), "+f"(d[16]), "+f"(d[17]), "+f"(d[18]), "+f"(d[19]), "+f"(d[20]), "+f"(d[21]), "+f"(d[22]), "+f"(d[23])
    : "r"(a0), "r"(a1), "r"(a2), "r"(a3), "l"(desc64<HI>(dlo)), "r"(acc), "n"(OFF >> 4));
}

template <uint32_t OFF, uint32_t HI, class D>
__device__ __forceinline__ void wgmma_n64(float* d, uint32_t a0, uint32_t a1, uint32_t a2, uint32_t a3, D dlo, int acc) {
  asm volatile("{ .reg .pred p; .reg .b64 ds; setp.ne.b32 p, %37, 0;\n"
    "add.u64 ds, %36, %38;\n"
    "wgmma.mma_async.sync.aligned.m64n64k16.f32.bf16.bf16 "
    "{%0, %1, %2, %3, %4, %5, %6, %7, %8, %9, %10, %11, %12, %13, %14, %15, %16, %17, %18, %19, %20, %21, %22, %23, %24, %25, %26, %27, %28, %29, %30, %31}, "
    "{%32, %33, %34, %35}, ds, p, 1, 1, 1; }"
    : "+f"(d[0]), "+f"(d[1]), "+f"(d[2]), "+f"(d[3]), "+f"(d[4]), "+f"(d[5]), "+f"(d[6]), "+f"(d[7]), "+f"(d[8]), "+f"(d[9]), "+f"(d[10]), "+f"(d[11]), "+f"(d[12]), "+f"(d[13]), "+f"(d[14]), "+f"(d[15]), "+f"(d[16]), "+f"(d[17]), "+f"(d[18]), "+f"(d[19]), "+f"(d[20]), "+f"(d[21]), "+f"(d[22]), "+f"(d[23]), "+f"(d[24]), "+f"(d[25]), "+f"(d[26]), "+f"(d[27]), "+f"(d[28]), "+f"(d[29]), "+f"(d[30]), "+f"(d[31])
    : "r"(a0), "r"(a1), "r"(a2), "r"(a3), "l"(desc64<HI>(dlo)), "r"(acc), "n"(OFF >> 4));
}

template <uint32_t OFF, uint32_t HI, class D>
__device__ __forceinline__ void wgmma_n128(float* d, uint32_t a0, uint32_t a1, uint32_t a2, uint32_t a3, D dlo, int acc) {
  asm volatile("{ .reg .pred p; .reg .b64 ds; setp.ne.b32 p, %69, 0;\n"
    "add.u64 ds, %68, %70;\n"
    "wgmma.mma_async.sync.aligned.m64n128k16.f32.bf16.bf16 "
    "{%0, %1, %2, %3, %4, %5, %6, %7, %8, %9, %10, %11, %12, %13, %14, %15, %16, %17, %18, %19, %20, %21, %22, %23, %24, %25, %26, %27, %28, %29, %30, %31, %32, %33, %34, %35, %36, %37, %38, %39, %40, %41, %42, %43, %44, %45, %46, %47, %48, %49, %50, %51, %52, %53, %54, %55, %56, %57, %58, %59, %60, %61, %62, %63}, "
    "{%64, %65, %66, %67}, ds, p, 1, 1, 1; }"
    : "+f"(d[0]), "+f"(d[1]), "+f"(d[2]), "+f"(d[3]), "+f"(d[4]), "+f"(d[5]), "+f"(d[6]), "+f"(d[7]), "+f"(d[8]), "+f"(d[9]), "+f"(d[10]), "+f"(d[11]), "+f"(d[12]), "+f"(d[13]), "+f"(d[14]), "+f"(d[15]), "+f"(d[16]), "+f"(d[17]), "+f"(d[18]), "+f"(d[19]), "+f"(d[20]), "+f"(d[21]), "+f"(d[22]), "+f"(d[23]), "+f"(d[24]), "+f"(d[25]), "+f"(d[26]), "+f"(d[27]), "+f"(d[28]), "+f"(d[29]), "+f"(d[30]), "+f"(d[31]), "+f"(d[32]), "+f"(d[33]), "+f"(d[34]), "+f"(d[35]), "+f"(d[36]), "+f"(d[37]), "+f"(d[38]), "+f"(d[39]), "+f"(d[40]), "+f"(d[41]), "+f"(d[42]), "+f"(d[43]), "+f"(d[44]), "+f"(d[45]), "+f"(d[46]), "+f"(d[47]), "+f"(d[48]), "+f"(d[49]), "+f"(d[50]), "+f"(d[51]), "+f"(d[52]), "+f"(d[53]), "+f"(d[54]), "+f"(d[55]), "+f"(d[56]), "+f"(d[57]), "+f"(d[58]), "+f"(d[59]), "+f"(d[60]), "+f"(d[61]), "+f"(d[62]), "+f"(d[63])
    : "r"(a0), "r"(a1), "r"(a2), "r"(a3), "l"(desc64<HI>(dlo)), "r"(acc), "n"(OFF >> 4));
}

template <uint32_t OFF, uint32_t HI, class D>
__device__ __forceinline__ void wgmma_n160(float* d, uint32_t a0, uint32_t a1, uint32_t a2, uint32_t a3, D dlo, int acc) {
  asm volatile("{ .reg .pred p; .reg .b64 ds; setp.ne.b32 p, %85, 0;\n"
    "add.u64 ds, %84, %86;\n"
    "wgmma.mma_async.sync.aligned.m64n160k16.f32.bf16.bf16 "
    "{%0, %1, %2, %3, %4, %5, %6, %7, %8, %9, %10, %11, %12, %13, %14, %15, %16, %17, %18, %19, %20, %21, %22, %23, %24, %25, %26, %27, %28, %29, %30, %31, %32, %33, %34, %35, %36, %37, %38, %39, %40, %41, %42, %43, %44, %45, %46, %47, %48, %49, %50, %51, %52, %53, %54, %55, %56, %57, %58, %59, %60, %61, %62, %63, %64, %65, %66, %67, %68, %69, %70, %71, %72, %73, %74, %75, %76, %77, %78, %79}, "
    "{%80, %81, %82, %83}, ds, p, 1, 1, 1; }"
    : "+f"(d[0]), "+f"(d[1]), "+f"(d[2]), "+f"(d[3]), "+f"(d[4]), "+f"(d[5]), "+f"(d[6]), "+f"(d[7]), "+f"(d[8]), "+f"(d[9]), "+f"(d[10]), "+f"(d[11]), "+f"(d[12]), "+f"(d[13]), "+f"(d[14]), "+f"(d[15]), "+f"(d[16]), "+f"(d[17]), "+f"(d[18]), "+f"(d[19]), "+f"(d[20]), "+f"(d[21]), "+f"(d[22]), "+f"(d[23]), "+f"(d[24]), "+f"(d[25]), "+f"(d[26]), "+f"(d[27]), "+f"(d[28]), "+f"(d[29]), "+f"(d[30]), "+f"(d[31]), "+f"(d[32]), "+f"(d[33]), "+f"(d[34]), "+f"(d[35]), "+f"(d[36]), "+f"(d[37]), "+f"(d[38]), "+f"(d[39]), "+f"(d[40]), "+f"(d[41]), "+f"(d[42]), "+f"(d[43]), "+f"(d[44]), "+f"(d[45]), "+f"(d[46]), "+f"(d[47]), "+f"(d[48]), "+f"(d[49]), "+f"(d[50]), "+f"(d[51]), "+f"(d[52]), "+f"(d[53]), "+f"(d[54]), "+f"(d[55]), "+f"(d[56]), "+f"(d[57]), "+f"(d[58]), "+f"(d[59]), "+f"(d[60]), "+f"(d[61]), "+f"(d[62]), "+f"(d[63]), "+f"(d[64]), "+f"(d[65]), "+f"(d[66]), "+f"(d[67]), "+f"(d[68]), "+f"(d[69]), "+f"(d[70]), "+f"(d[71]), "+f"(d[72]), "+f"(d[73]), "+f"(d[74]), "+f"(d[75]), "+f"(d[76]), "+f"(d[77]), "+f"(d[78]), "+f"(d[79])
    : "r"(a0), "r"(a1), "r"(a2), "r"(a3), "l"(desc64<HI>(dlo)), "r"(acc), "n"(OFF >> 4));
}

template <uint32_t OFF, uint32_t HI, class D>
__device__ __forceinline__ void wgmma_ss_n24(float* d, uint32_t alo, D dlo) {
  asm volatile("{ .reg .b64 ds, da;\n"
    "add.u64 ds, %13, %14; mov.b64 da, {%12, 16};\n"
    "wgmma.mma_async.sync.aligned.m64n24k16.f32.bf16.bf16 "
    "{%0, %1, %2, %3, %4, %5, %6, %7, %8, %9, %10, %11}, "
    "da, ds, 1, 1, 1, 0, 1; }"
    : "+f"(d[0]), "+f"(d[1]), "+f"(d[2]), "+f"(d[3]), "+f"(d[4]), "+f"(d[5]), "+f"(d[6]), "+f"(d[7]), "+f"(d[8]), "+f"(d[9]), "+f"(d[10]), "+f"(d[11])
    : "r"(alo), "l"(desc64<HI>(dlo)), "n"(OFF >> 4));
}

template <uint32_t OFF, uint32_t HI, class D>
__device__ __forceinline__ void wgmma_ss_n48(float* d, uint32_t alo, D dlo) {
  asm volatile("{ .reg .b64 ds, da;\n"
    "add.u64 ds, %25, %26; mov.b64 da, {%24, 16};\n"
    "wgmma.mma_async.sync.aligned.m64n48k16.f32.bf16.bf16 "
    "{%0, %1, %2, %3, %4, %5, %6, %7, %8, %9, %10, %11, %12, %13, %14, %15, %16, %17, %18, %19, %20, %21, %22, %23}, "
    "da, ds, 1, 1, 1, 0, 1; }"
    : "+f"(d[0]), "+f"(d[1]), "+f"(d[2]), "+f"(d[3]), "+f"(d[4]), "+f"(d[5]), "+f"(d[6]), "+f"(d[7]), "+f"(d[8]), "+f"(d[9]), "+f"(d[10]), "+f"(d[11]), "+f"(d[12]), "+f"(d[13]), "+f"(d[14]), "+f"(d[15]), "+f"(d[16]), "+f"(d[17]), "+f"(d[18]), "+f"(d[19]), "+f"(d[20]), "+f"(d[21]), "+f"(d[22]), "+f"(d[23])
    : "r"(alo), "l"(desc64<HI>(dlo)), "n"(OFF >> 4));
}

template <uint32_t OFF, uint32_t HI, class D>
__device__ __forceinline__ void wgmma_ss_n64(float* d, uint32_t alo, D dlo) {
  asm volatile("{ .reg .b64 ds, da;\n"
    "add.u64 ds, %33, %34; mov.b64 da, {%32, 16};\n"
    "wgmma.mma_async.sync.aligned.m64n64k16.f32.bf16.bf16 "
    "{%0, %1, %2, %3, %4, %5, %6, %7, %8, %9, %10, %11, %12, %13, %14, %15, %16, %17, %18, %19, %20, %21, %22, %23, %24, %25, %26, %27, %28, %29, %30, %31}, "
    "da, ds, 1, 1, 1, 0, 1; }"
    : "+f"(d[0]), "+f"(d[1]), "+f"(d[2]), "+f"(d[3]), "+f"(d[4]), "+f"(d[5]), "+f"(d[6]), "+f"(d[7]), "+f"(d[8]), "+f"(d[9]), "+f"(d[10]), "+f"(d[11]), "+f"(d[12]), "+f"(d[13]), "+f"(d[14]), "+f"(d[15]), "+f"(d[16]), "+f"(d[17]), "+f"(d[18]), "+f"(d[19]), "+f"(d[20]), "+f"(d[21]), "+f"(d[22]), "+f"(d[23]), "+f"(d[24]), "+f"(d[25]), "+f"(d[26]), "+f"(d[27]), "+f"(d[28]), "+f"(d[29]), "+f"(d[30]), "+f"(d[31])
    : "r"(alo), "l"(desc64<HI>(dlo)), "n"(OFF >> 4));
}

template <uint32_t OFF, uint32_t HI, class D>
__device__ __forceinline__ void wgmma_ss_n128(float* d, uint32_t alo, D dlo) {
  asm volatile("{ .reg .b64 ds, da;\n"
    "add.u64 ds, %65, %66; mov.b64 da, {%64, 16};\n"
    "wgmma.mma_async.sync.aligned.m64n128k16.f32.bf16.bf16 "
    "{%0, %1, %2, %3, %4, %5, %6, %7, %8, %9, %10, %11, %12, %13, %14, %15, %16, %17, %18, %19, %20, %21, %22, %23, %24, %25, %26, %27, %28, %29, %30, %31, %32, %33, %34, %35, %36, %37, %38, %39, %40, %41, %42, %43, %44, %45, %46, %47, %48, %49, %50, %51, %52, %53, %54, %55, %56, %57, %58, %59, %60, %61, %62, %63}, "
    "da, ds, 1, 1, 1, 0, 1; }"
    : "+f"(d[0]), "+f"(d[1]), "+f"(d[2]), "+f"(d[3]), "+f"(d[4]), "+f"(d[5]), "+f"(d[6]), "+f"(d[7]), "+f"(d[8]), "+f"(d[9]), "+f"(d[10]), "+f"(d[11]), "+f"(d[12]), "+f"(d[13]), "+f"(d[14]), "+f"(d[15]), "+f"(d[16]), "+f"(d[17]), "+f"(d[18]), "+f"(d[19]), "+f"(d[20]), "+f"(d[21]), "+f"(d[22]), "+f"(d[23]), "+f"(d[24]), "+f"(d[25]), "+f"(d[26]), "+f"(d[27]), "+f"(d[28]), "+f"(d[29]), "+f"(d[30]), "+f"(d[31]), "+f"(d[32]), "+f"(d[33]), "+f"(d[34]), "+f"(d[35]), "+f"(d[36]), "+f"(d[37]), "+f"(d[38]), "+f"(d[39]), "+f"(d[40]), "+f"(d[41]), "+f"(d[42]), "+f"(d[43]), "+f"(d[44]), "+f"(d[45]), "+f"(d[46]), "+f"(d[47]), "+f"(d[48]), "+f"(d[49]), "+f"(d[50]), "+f"(d[51]), "+f"(d[52]), "+f"(d[53]), "+f"(d[54]), "+f"(d[55]), "+f"(d[56]), "+f"(d[57]), "+f"(d[58]), "+f"(d[59]), "+f"(d[60]), "+f"(d[61]), "+f"(d[62]), "+f"(d[63])
    : "r"(alo), "l"(desc64<HI>(dlo)), "n"(OFF >> 4));
}

struct Params {
  CUtensorMap wqkv, wtail, wg, wu, wd, wo, out128, out64, wg32, wu32, wd4;
};

__device__ __forceinline__ void softmax8(float* p, int pos) {
  constexpr float SC = 4 * 0.23570226039551584f;
  if (pos < 14) {
#pragma unroll
    for (int j = 1; j < 8; j++) p[j] = pos >= 2 * j ? p[j] : -1e9f / SC;
  }
  float mx = p[0];
#pragma unroll
  for (int j = 1; j < 8; j++) mx = fmaxf(mx, p[j]);
  const float off = mx * (-SC * 1.4426950408889634f);
  float sum = 0.f;
#pragma unroll
  for (int j = 0; j < 8; j++) { p[j] = ex2(fmaf(p[j], SC * 1.4426950408889634f, off)); sum += p[j]; }
  const float inv = 2.f * rcp(sum);
#pragma unroll
  for (int j = 0; j < 8; j++) p[j] *= inv;
}
__device__ __forceinline__ void attn_unit(uint32_t sb, int unit, int lane, int pos0) {
  const int row = unit * 16 + ((lane >> 2) & 1) + (lane >> 3) * 4;
  uint32_t a = sb + OFF_QKV + (lane & 3) * 36 + row * QPITCH;
  float p0[8], p1[8];
#pragma unroll
  for (int j = 0; j < 8; j++) { p0[j] = 0.f; p1[j] = 0.f; }
#pragma unroll 1
  for (const uint32_t e = a + 36; a != e; a += 4) {
    uint32_t v[9];
    const uint32_t qa = lds32(a), qb = lds32(a + 2 * QPITCH);
#pragma unroll
    for (int j = 0; j < 9; j++) v[j] = lds32(a + 144 - (j - 1) * 2 * QPITCH);
    const float qa0 = blo(qa), qa1 = bhi(qa), qb0 = blo(qb), qb1 = bhi(qb);
#pragma unroll
    for (int j = 0; j < 9; j++) {
      const float lo = blo(v[j]), hi = bhi(v[j]);
      if (j < 8) p1[j] = fmaf(qb1, hi, fmaf(qb0, lo, p1[j]));
      if (j > 0) p0[j - 1] = fmaf(qa1, hi, fmaf(qa0, lo, p0[j - 1]));
    }
  }
  softmax8(p0, pos0 + row);
  softmax8(p1, pos0 + row + 2);
#pragma unroll 1
  for (const uint32_t e = a + 36; a != e; a += 4) {
    uint32_t v[9];
#pragma unroll
    for (int j = 0; j < 9; j++) v[j] = lds32(a + 288 - 36 - (j - 1) * 2 * QPITCH);
    float oa0 = 0.f, oa1 = 0.f, ob0 = 0.f, ob1 = 0.f;
#pragma unroll
    for (int j = 0; j < 9; j++) {
      const float lo = blo(v[j]), hi = bhi(v[j]);
      if (j < 8) { ob0 = fmaf(p1[j], lo, ob0); ob1 = fmaf(p1[j], hi, ob1); }
      if (j > 0) { oa0 = fmaf(p0[j - 1], lo, oa0); oa1 = fmaf(p0[j - 1], hi, oa1); }
    }
    sts32(a - 36, pack2(oa0, oa1));
    sts32(a - 36 + 2 * QPITCH, pack2(ob0, ob1));
  }
}

__device__ __forceinline__ void pause(uint32_t clocks) {
  uint32_t t0, t;
  asm volatile("mov.u32 %0, %%clock;" : "=r"(t0));
  do { __nanosleep(100); asm volatile("mov.u32 %0, %%clock;" : "=r"(t)); } while (t - t0 < clocks);
}
__device__ __forceinline__ void fetch_x(uint32_t sb, const __nv_bfloat16* x, int m, int w, int slot, int lane) {
  const unsigned char* src = reinterpret_cast<const unsigned char*>(x + (size_t)(m * 128 + w * 16 + (lane >> 3)) * DM) + (lane & 7) * 16;
  const uint32_t d0 = sb + slot * SLOT + ((lane * 16) ^ ((lane >> 3) << 4));
#pragma unroll
  for (int j = 0; j < 9; j++) {
#pragma unroll
    for (int i = 0; i < 4; i++) cp_async16(((i & 1) ? d0 ^ 64 : d0) + j * 2048 + i * 512, src + i * 4608 + j * 128);
    if ((j & 1) || j == 8) asm volatile("cp.async.commit_group;" ::: "memory");
  }
}

__device__ __forceinline__ void spare_consumer(uint32_t sb, const __nv_bfloat16* x, int warp) {
  const int lane = tid_now() & 31;
  int m;
  asm volatile("mov.u32 %0, %%ctaid.x;" : "=r"(m));
  m &= 3;
  pause(SPARE_DELAY);
  fetch_x(sb, x, m, warp, 4 + warp, lane);
  const uint32_t bars = sb + OFF_BAR, ebar = mapa(bars + BAR_EMPTY, lane & 1), desc = desc_lo(sb, 4096);
  const uint32_t xb = sb + (4 + warp) * SLOT + (lane & 15) * 128 + (((lane >> 4) ^ (lane & 7)) << 4);
#pragma unroll 1
  for (int j = 0; j < 4; j++, m += 4) {
    uint32_t xa[144];
    float ca[4][4], cb[4][4], cs[4][4];
#pragma unroll
    for (int i = 0; i < 16; i++) { ca[i >> 2][i & 3] = 0.f; cb[i >> 2][i & 3] = 0.f; cs[i >> 2][i & 3] = 0.f; }
    asm volatile("cp.async.wait_all;" ::: "memory");
    __syncwarp();
#pragma unroll
    for (int i = 0; i < 36; i++) {
      uint32_t* a = xa + 4 * i;
      asm volatile("ldmatrix.sync.aligned.m8n8.x4.shared.b16 {%0,%1,%2,%3}, [%4];"
                   : "=r"(a[0]), "=r"(a[1]), "=r"(a[2]), "=r"(a[3]) : "r"((xb ^ ((i & 3) << 5)) + (i >> 2) * 2048) : "memory");
    }
#pragma unroll
    for (int i = 0; i < 36; i++) {
      const uint32_t* a = xa + 4 * i;
      mma16816(cs[i & 3], a[0], a[1], a[2], a[3], 0x3f803f80u, 0x3f803f80u);
      mma1688(ca[(2 * i) & 3], a[0], a[1], a[0]); mma1688(cb[(2 * i) & 3], a[0], a[1], a[1]);
      mma1688(ca[(2 * i + 1) & 3], a[2], a[3], a[2]); mma1688(cb[(2 * i + 1) & 3], a[2], a[3], a[3]);
    }
#pragma unroll
    for (int i = 0; i < 8; i++) { ca[i >> 2][i & 3] += ca[2 + (i >> 2)][i & 3]; cb[i >> 2][i & 3] += cb[2 + (i >> 2)][i & 3]; cs[i >> 2][i & 3] += cs[2 + (i >> 2)][i & 3]; }
    const int rr = lane >> 2, src = rr * 4 + (rr >> 1);
    const bool odd = rr & 1;
    const float q0 = __shfl_sync(0xffffffff, odd ? ca[0][1] + ca[1][1] : ca[0][0] + ca[1][0], src);
    const float q1 = __shfl_sync(0xffffffff, odd ? cb[0][3] + cb[1][3] : cb[0][2] + cb[1][2], src);
    const float m0 = (cs[0][0] + cs[1][0]) * (1.0f / DM), m1 = (cs[0][2] + cs[1][2]) * (1.0f / DM);
    const float hr0 = 0.5f * rsqrtf(fmaxf(q0 * (1.0f / DM) - m0 * m0, 0.f) + 1e-5f);
    const float hr1 = 0.5f * rsqrtf(fmaxf(q1 * (1.0f / DM) - m1 * m1, 0.f) + 1e-5f);
    center<144>(xa, pack2(m0, m0), pack2(m1, m1));
#pragma unroll 1
    for (int s = 0; s < 4; s++) {
      float acc[32];
      const bool rel = lane < 2 && j * s != 9;
      const unsigned char* src = reinterpret_cast<const unsigned char*>(x + (size_t)((m + 4) * 128 + warp * 16 + s * 4 + (lane >> 3)) * DM) + (lane & 7) * 16;
      const uint32_t dst = (sb + (4 + warp) * SLOT + s * 512 + ((lane * 16) ^ ((lane >> 3) << 4))) ^ ((s & 1) << 6);
      static_for<0, 9>([&](auto KB) {
        constexpr int kb = decltype(KB)::value;
        if (kb == 5 && warp >= 4) named_sync(4, 256);
        mbar_wait(bars + BAR_FULL + 8 * kb, s & 1);
        wg_fence();
        static_for<0, 4>([&](auto I) {
          constexpr int i = decltype(I)::value;
          const uint32_t* a = xa + 16 * kb + 4 * i;
          wgmma_n64<kb * 8192 + i * 1024, HI64>(acc, a[0], a[1], a[2], a[3], desc, kb + i);
        });
        wg_commit();
        if (kb == 8 && warp < 4) named_arrive(4, 256);
        if (j < 3) cp_async16(dst + kb * 2048, src + kb * 128);
        if constexpr (kb > 0) { wg_wait<1>(); if (rel) mbar_arrive_cl1(ebar + 8 * (kb - 1)); }
      });
      wg_wait<0>();
      if (rel) mbar_arrive_cl1(ebar + 8 * 8);
      keep<32>(acc);
      uint4* hp = g_s.a2 + ((m * 4 + s) * 8 + warp) * NP2 * 32 + lane;
#pragma unroll
      for (int i = 0; i < 2; i++) {
        uint4 v;
        v.x = pack2(glu(acc[8 * i], acc[16 + 8 * i], hr0), glu(acc[8 * i + 1], acc[16 + 8 * i + 1], hr0));
        v.y = pack2(glu(acc[8 * i + 2], acc[16 + 8 * i + 2], hr1), glu(acc[8 * i + 3], acc[16 + 8 * i + 3], hr1));
        v.z = pack2(glu(acc[8 * i + 4], acc[16 + 8 * i + 4], hr0), glu(acc[8 * i + 5], acc[16 + 8 * i + 5], hr0));
        v.w = pack2(glu(acc[8 * i + 6], acc[16 + 8 * i + 6], hr1), glu(acc[8 * i + 7], acc[16 + 8 * i + 7], hr1));
        hp[i * 32] = v; hp[(81 + i) * 32] = v;
      }
    }
    __syncwarp();
    if (lane == 0) mbar_arrive(bars + BAR_FL + 8 * (2 * j + (warp >> 2)));
  }
}

template <bool SPARE_FIRST>
__global__ void __cluster_dims__(2, 1, 1) __launch_bounds__(384, 1)
fused_kernel(const __nv_bfloat16* __restrict__ x, __nv_bfloat16* __restrict__ out, const __grid_constant__ Params P) {
  extern __shared__ __align__(1024) unsigned char smem_raw[];
  const uint32_t sb = smem_u32(smem_raw);
  if (sb & 1023) __trap();
  const uint32_t bars = sb + OFF_BAR;
  const int lane = threadIdx.x & 31;
  const int bid = SPARE_FIRST ? (blockIdx.x + 128) % 132 : blockIdx.x;
  const int rank = bid & 1, u = bid >> 1, unit = SPARE_FIRST ? u : u < 4 ? 8 * u + 33 : u - 4 + (max(37 * u - 1110, 0) >> 8);
  const int g = unit >> 3, m = (unit & 7) * 2 + rank;
  const int s = g >> 1, c = g & 1;

#define XSLOT(w) (4 + ((w) & 4) + (((w) + 3 - s) & 3))
  unsigned epoch0 = 0;
  if (threadIdx.x < 256 && g != 8) {
    const int w = threadIdx.x >> 5;
    if (w >= 4) named_sync(5, 256);
    fetch_x(sb, x, m, w, XSLOT(w), lane);
    if (w < 4) named_arrive(5, 256);
  } else if (threadIdx.x == 352) {
    asm volatile("ld.global.cg.u32 %0, [%1];" : "=r"(epoch0) : "l"(&g_s.ctr[blockIdx.x * FS]) : "memory");
  }
  const int warp = __shfl_sync(0xffffffff, threadIdx.x >> 5, 0);
  if (warp == 8) {
    if (elect_one()) {
      prefetch_map(&P.wqkv);
      for (int i = 0; i < NSLOT; i++) { mbar_init(bars + BAR_FULL + 8 * i, 1); mbar_init(bars + BAR_EMPTY + 8 * i, 16); }
      for (int i = 0; i < 10; i++) mbar_init(bars + BAR_FL + 8 * i, 4);
      mbar_init(bars + BAR_X0, 4); mbar_init(bars + BAR_X1E, 4); mbar_init(bars + BAR_X1, 4); mbar_init(bars + BAR_XDONE, 4);
      mbar_init(bars + BAR_X0F, 4); mbar_init(bars + BAR_STAT, 1); mbar_init(bars + BAR_STAT + 8, 1); mbar_init(bars + BAR_QKV0, 4); mbar_init(bars + BAR_QKV1, 4);
      mbar_init(bars + BAR_H5, 8); mbar_init(bars + BAR_HDONE, 8);
      mbar_init(bars + BAR_STG, 64); mbar_init(bars + BAR_DEPS, 1); mbar_init(bars + BAR_DEPH, 1); mbar_init(bars + BAR_DEPX, 1); mbar_init(bars + BAR_AXW, 1);
      asm volatile("fence.mbarrier_init.release.cluster;" ::: "memory");
    }
    __syncwarp();
  }
  asm volatile("barrier.cluster.arrive.relaxed.aligned;" ::: "memory");
  asm volatile("barrier.cluster.wait.aligned;" ::: "memory");

  if (g == 8 && warp < 8) {
    asm volatile("setmaxnreg.inc.sync.aligned.u32 232;");
    spare_consumer(sb, x, warp); return;
  }
  if (warp >= 8) {
    asm volatile("setmaxnreg.dec.sync.aligned.u32 40;");
    if (warp == 8) {
      if (elect_one()) {
        uint64_t pol;
        if (g == 8) {
          asm volatile("createpolicy.fractional.L2::evict_normal.b64 %0, 1.0;" : "=l"(pol));
          pause(SPARE_DELAY);
#pragma unroll 1
          for (int n = 0; n < 16; n++) {
#pragma unroll 1
            for (int kb = 0; kb < 9; kb++) {
              mbar_wait(bars + BAR_EMPTY + 8 * kb, ~n & 1);
              mbar_expect_tx(bars + BAR_FULL + 8 * kb, 8192);
              tma_2d_mc(sb + kb * 8192 + rank * 4096, rank ? &P.wu32 : &P.wg32, 1152 * (n & 3) + 512, kb * 64, bars + BAR_FULL + 8 * kb, pol);
            }
          }
          return;
        }
        asm volatile("createpolicy.fractional.L2::evict_first.b64 %0, 1.0;" : "=l"(pol));
#pragma unroll 1
        for (int kb = 0; kb < 9; kb++) {
          if (kb == 0) mbar_wait(bars + BAR_X0, 0);
          if (kb == 2) mbar_wait(bars + BAR_X1E, 0);
          mbar_wait(bars + BAR_EMPTY + 8 * kb, kb < 4);
          mbar_expect_tx(bars + BAR_FULL + 8 * kb, 16384);
          tma_2d_mc(sb + kb * SLOT + rank * 8192, &P.wqkv, rank * 576 + 72 * g + 8 * c, kb * 64, bars + BAR_FULL + 8 * kb, pol);
          if (kb == 3) {
            prefetch_map(&P.wtail); prefetch_map(&P.wg); prefetch_map(&P.wu);
            prefetch_map(&P.wd); prefetch_map(&P.wo); prefetch_map(&P.out128); prefetch_map(&P.out64);
          }
        }
#pragma unroll 1
        for (int kb = 0; kb < 9; kb++) {
          mbar_wait(bars + BAR_EMPTY + 8 * kb, kb >= 4);
          mbar_expect_tx(bars + BAR_FULL + 8 * kb, 8192 + 3072);
          if (rank) tma_3d_mc(sb + kb * SLOT + 8192 + 2048, &P.wtail, 72 * g + 64 - 64 * c, kb * 64, 2, bars + BAR_FULL + 8 * kb, pol);
          else tma_2d_mc(sb + kb * SLOT, &P.wqkv, 1152 + 72 * g + 8 * c, kb * 64, bars + BAR_FULL + 8 * kb, pol);
          tma_3d_mc(sb + kb * SLOT + 8192 + rank * 1024, &P.wtail, 72 * g + 64 - 64 * c, kb * 64, rank, bars + BAR_FULL + 8 * kb, pol);
        }
        {
          const CUtensorMap* mp = rank ? &P.wu : &P.wg;
          int col = 576 * g + (c ? 512 : 0);
#pragma unroll 1
          for (int t = 2; t < 11; t++, col += c ? -64 : 64) {
#pragma unroll 1
            for (int kb = 0; kb < 9; kb++) {
              mbar_wait(bars + BAR_EMPTY + 8 * kb, (t + (kb < 4)) & 1);
              mbar_expect_tx(bars + BAR_FULL + 8 * kb, 16384);
              tma_2d_mc(sb + kb * SLOT + rank * 8192, mp, col + (t == 10 ? 32 - 32 * c : 0), kb * 64, bars + BAR_FULL + 8 * kb, pol);
            }
          }
        }
        int slot = 0, k = 11;
#pragma unroll 1
        for (int n = 0; n <= 40; n++) {
          const int t = 2 * n + rank;
          const int p = c ? max(79 - 2 * n, 0) + rank : t + 2;
          const bool is_o = p >= 37 && p < 46;
          int row = is_o ? 144 * s + 16 * (p - 37) : 1152 * s + 16 * (p < 2 ? p + 32 : p < 34 ? p - 2 : p < 37 ? p : p < 81 ? p - 9 : p - 49);
          const CUtensorMap* mp = is_o ? &P.wo : &P.wd;
          uint32_t dst = sb + slot * SLOT + rank * 9216, bytes = n < 40 ? 18432 : 9216;
          asm volatile("" : "+r"(row), "+l"(mp), "+r"(dst), "+r"(bytes));
          if (t == 81) { mbar_wait(bars + BAR_EMPTY + 8 * 4, 1); mbar_expect_tx(bars + BAR_FULL + 8 * 4, 9216); break; }
          mbar_wait(bars + BAR_EMPTY + 8 * slot, (k + (slot < 4)) & 1);
          mbar_expect_tx(bars + BAR_FULL + 8 * slot, bytes);
          tma_3d_mc(dst, mp, 0, row, 9 * c, bars + BAR_FULL + 8 * slot, pol);
          if (n == 8) {
            mbar_expect_tx(bars + BAR_AXW, 4096);
            if (rank) tma_3d_mc(sb + OFF_AX, &P.wd4, 0, 1152 * s + 528 - 16 * c, 14 * c, bars + BAR_AXW, pol);
          }
          if (++slot == NSLOT) { slot = 0; k++; }
        }
#pragma unroll 1
        for (int i = 0; i < 10; i++) {
          const int w = i >= 5, p = i - 5 * w, row = m * 128 + w * 64;
          const uint32_t stg = sb + OFF_AST + w * 4 * AST_WARP;
          const int col = p == 4 ? 256 + 32 * c : c ? 448 - 128 * (p >> 1) + 64 * (p & 1) : 64 * p;
          mbar_wait(bars + BAR_FL + 8 * i, 0);
          asm volatile("fence.proxy.async.shared::cta;" ::: "memory");
          tma_red_2d(p < 4 ? &P.out128 : &P.out64, col, row, p == 3 ? sb + 5 * SLOT + w * 8192 : stg + (p < 3 ? p : 3) * 8192);
        }
        asm volatile("cp.async.bulk.commit_group;\n cp.async.bulk.wait_group.read 0;" ::: "memory");
      }
    } else {
      const int ht = threadIdx.x - 288, hw = warp - 9;
      if (ht == 64) {
        unsigned e;
        asm volatile("add.u32 %0, %1, 1;" : "=r"(e) : "r"(epoch0));
        g_s.ctr[blockIdx.x * FS] = e;
        sts32(bars + OFF_EPOCH, e);
        if (g == 8) {
#pragma unroll 1
          for (int j = 0; j < 4; j++) {
            mbar_wait(bars + BAR_FL + 16 * j, 0); mbar_wait(bars + BAR_FL + 16 * j + 8, 0);
            flag_set(&g_s.flag_o[(((blockIdx.x & 3) + 4 * j) * 9 + 8) * FS], e);
          }
        }
      }
      if (g == 8) return;
      named_sync(1, 96);
      const unsigned epoch = lds32(bars + OFF_EPOCH);
      if (hw < 2) {
#pragma unroll 1
        for (int w = 0; w < 2; w++) {
          const uint32_t a0 = sb + (7 + 4 * w) * SLOT + c * 1024 + ht * 16;
          uint2* dst = g_s.stat + m * 128 + w * 64 + 8 * g + (ht >> 3);
          float q0 = 0.f, q1 = 0.f;
          mbar_wait(bars + BAR_X0F + 16 * w, 0);
#pragma unroll 1
          for (uint32_t a = a0; a < a0 + SLOT; a += 3 * 2048) {
            const uint4 u = lds128(a), v = lds128(a + 2048), y = lds128(a + 4096);
            const uint32_t z[12] = {u.x, u.y, u.z, u.w, v.x, v.y, v.z, v.w, y.x, y.y, y.z, y.w};
#pragma unroll
            for (int i = 0; i < 12; i++) { const float lo = blo(z[i]), hi = bhi(z[i]); q0 = fmaf(lo, lo, q0); q1 = fmaf(hi, hi, q1); }
          }
          q0 += q1;
          if (computed(q0) && lane < 2 && w == 0) mbar_arrive_cl(mapa(bars + BAR_EMPTY + 8 * 7, lane), 2);
#pragma unroll
          for (int o = 1; o < 8; o *= 2) q0 += __shfl_xor_sync(0xffffffff, q0, o);
          if ((lane & 7) == 0) asm volatile("{ .reg .b64 t; mov.b64 t, {%1, %2}; st.relaxed.gpu.global.b64 [%0], t; }" ::"l"(dst), "f"(q0), "r"(epoch) : "memory");
        }
      }
      named_sync(1, 96);
      mbar_wait(bars + BAR_XDONE, 0);
      if (hw == 2) {
#pragma unroll 1
        for (int w = 0; w < 2; w++) {
          unsigned n = 0;
          uint32_t v0, t0, v1, t1;
          const uint2* sp = g_s.stat + m * 128 + w * 64 + 2 * lane;
          while (true) {
            asm volatile("{ .reg .b64 a, b; ld.relaxed.gpu.global.v2.b64 {a, b}, [%4]; mov.b64 {%0, %1}, a; mov.b64 {%2, %3}, b; }"
                         : "=r"(v0), "=r"(t0), "=r"(v1), "=r"(t1) : "l"(sp) : "memory");
            if (__all_sync(0xffffffff, t0 == epoch && t1 == epoch)) break;
            if (++n > SPIN_LIMIT) __trap();
            __nanosleep(200);
          }
          const uint32_t a = sb + OFF_HALO + (2 * w + (lane >> 4)) * QPITCH + (lane & 15) * 8;
          sts32(a, v0); sts32(a + 4, v1);
          __syncwarp();
          if (lane == 0) mbar_arrive(bars + BAR_STAT + 8 * w);
        }
      }
      named_sync(1, 96);
      mbar_wait(bars + BAR_QKV0, 0);
#pragma unroll 1
      for (int it = 0; it < 3; it++) {
        int unit = 1 + hw + 3 * it;
        if (it == 1) {
          mbar_wait(bars + BAR_QKV1, 0);
          if (m < 15) {
            uint4* hd = g_s.halo + (m * 8 + g) * 252;
#pragma unroll 1
            for (int i = tid_now() - 288; i < 252; i += 96) { const int r = i / 18, ch = i - r * 18; hd[i] = lds128(sb + OFF_QKV + (114 + r) * QPITCH + 144 + ch * 16); }
            named_sync(1, 96);
            if (ht == 0) flag_set(&g_s.flag_halo[(m * 8 + g) * FS], epoch);
          }
        }
        if (it == 2) {
          if (hw == 2) unit = 0;
          if (m > 0) {
            if (lane == 0) flag_wait(&g_s.flag_halo[((m - 1) * 8 + g) * FS], epoch);
            __syncwarp();
          }
          const uint4* hs = g_s.halo + ((m - 1) * 8 + g) * 252;
#pragma unroll 1
          for (int i = tid_now() - 288; i < 252; i += 96) {
            const int r = i / 18, ch = i - r * 18;
            sts128(sb + OFF_HALO + r * QPITCH + 144 + ch * 16, m > 0 ? ldg_cg(hs + i) : lds128(sb + OFF_QKV + 144 + ch * 16));
          }
          named_sync(1, 96);
        }
        if (unit < 8) {
          attn_unit(sb, unit, lane, m * 128);
        } else {
          const int ln = tid_now() & 31, off = (m * 128 + 32 * s + (ln >> 2)) * 72 + 36 * c + (ln & 3);
          const uint4* xs = reinterpret_cast<const uint4*>(x) + off;
          uint4* od = reinterpret_cast<uint4*>(out) + off;
#pragma unroll 1
          for (int i = 0; i < 36; i += 4) {
            uint4 v[4];
#pragma unroll
            for (int j = 0; j < 4; j++) v[j] = __ldg(xs + i + j * 8 * 72);
#pragma unroll
            for (int j = 0; j < 4; j++) od[i + j * 8 * 72] = v[j];
          }
          asm volatile("fence.proxy.async.global;" ::: "memory");
          __syncwarp();
        }
      }
      named_sync(1, 96);
      {
        uint4* ao = g_s.a2 + (m * 4 + s) * NP2 * 256 + 37 * 32;
#pragma unroll 1
        for (int i = hw; i < 40; i += 3) {
          const int ks = i >> 3, wr = i & 7;
          const uint32_t a = sb + OFF_QKV + (wr * 16 + (lane >> 2)) * QPITCH + (lane & 3) * 4 + (ks < 4 ? ks * 32 + c * 16 : c ? 0 : 128);
          const uint32_t w0 = lds32(a), w1 = lds32(a + 8 * QPITCH);
          if (ks < 4) ao[(wr * NP2 + ks + 5 * c) * 32 + lane] = make_uint4(w0, w1, lds32(a + 16), lds32(a + 8 * QPITCH + 16));
          else reinterpret_cast<uint2*>(ao + (wr * NP2 + 4) * 32 + lane)[c] = make_uint2(w0, w1);
        }
      }
      named_sync(1, 96);
      if (hw > 0) {
        mbar_wait(bars + BAR_H5, 0);
        const uint4* src = g_s.a2 + ((m * 4 + s) * 8 + (hw - 1) * 4) * NP2 * 32 + (c ? 79 * 32 : 64) + lane;
        uint32_t dst = sb + OFF_AST + (hw - 1) * 4 * AST_WARP + lane * 16;
#pragma unroll 1
        for (int w = 0; w < 4; w++, src += NP2 * 32, dst += AST_WARP) {
          const uint4* sp = src;
#pragma unroll 1
          for (int u = 0; u < 7; u++, sp += c ? -64 : 64) {
            cp_async16(dst + u * 1024, sp);
            cp_async16(dst + u * 1024 + 512, sp + 32);
          }
        }
        asm volatile("cp.async.mbarrier.arrive.noinc.shared::cta.b64 [%0];" ::"r"(bars + BAR_STG) : "memory");
      }
      if (hw == 0) {
        if (lane == 0) flag_set(&g_s.flag_o[(m * 9 + g) * FS], epoch);
        if (lane < 8) flag_wait(&g_s.flag_o[(m * 9 + lane) * FS], epoch);
        __syncwarp();
        if (lane == 0) { mbar_arrive(bars + BAR_DEPS); flag_wait(&g_s.flag_o[(m * 9 + 8) * FS], epoch); mbar_arrive(bars + BAR_DEPX); }
      }
      if (hw == 2) {
        mbar_wait(bars + BAR_HDONE, 0);
        if (lane == 0) { flag_set(&g_s.flag_h[(m * 8 + g) * FS], epoch); flag_wait(&g_s.flag_h[(m * 8 + (g ^ 1)) * FS], epoch); mbar_arrive(bars + BAR_DEPH); }
      }
      asm volatile("cp.async.wait_all;" ::: "memory");
    }
  } else {
    asm volatile("setmaxnreg.inc.sync.aligned.u32 232;");
    const int wg = warp >> 2, wi = warp & 3;
    const uint32_t ebar = mapa(bars + BAR_EMPTY, lane & 1);
    uint32_t xa[144], mm0, mm1;
    float r0, r1;
    {
      const uint32_t xb = sb + XSLOT(warp) * SLOT + (lane & 15) * 128 + (((lane >> 4) ^ (lane & 7)) << 4);
      float cs[4][4];
#pragma unroll
      for (int i = 0; i < 16; i++) cs[i >> 2][i & 3] = 0.f;
#pragma unroll
      for (int j = 0; j < 9; j++) {
        if (j % 2 == 0) {
          switch (j) {
            case 0: asm volatile("cp.async.wait_group 4;" ::: "memory"); break;
            case 2: asm volatile("cp.async.wait_group 3;" ::: "memory"); break;
            case 4: asm volatile("cp.async.wait_group 2;" ::: "memory"); break;
            case 6: asm volatile("cp.async.wait_group 1;" ::: "memory"); break;
            default: asm volatile("cp.async.wait_group 0;" ::: "memory"); break;
          }
          __syncwarp();
          if (j == 2 && lane == 0 && !wg) mbar_arrive(bars + BAR_X0);
          if (j == 6 && lane == 0 && wg) mbar_arrive(bars + BAR_X1E);
          if (j == 8 && lane == 0) mbar_arrive(bars + (wg ? BAR_X1 : BAR_X0F));
        }
#pragma unroll
        for (int i = 0; i < 4; i++) {
          uint32_t* a = xa + 16 * j + 4 * i;
          asm volatile("ldmatrix.sync.aligned.m8n8.x4.shared.b16 {%0,%1,%2,%3}, [%4];"
                       : "=r"(a[0]), "=r"(a[1]), "=r"(a[2]), "=r"(a[3])
                       : "r"((xb ^ (i << 5)) + j * 2048) : "memory");
        }
        if ((j & 1) || j == 8) {
#pragma unroll
          for (int i = 0; i < (j == 8 ? 4 : 8); i++) {
            const uint32_t* a = xa + 16 * (j & ~1) + 4 * i;
            mma16816(cs[i & 3], a[0], a[1], a[2], a[3], 0x3f803f80u, 0x3f803f80u);
          }
        }
      }
      const float s0 = (cs[0][0] + cs[1][0]) + (cs[2][0] + cs[3][0]), s1 = (cs[0][2] + cs[1][2]) + (cs[2][2] + cs[3][2]);
      const float m0 = s0 * (1.0f / DM), m1 = s1 * (1.0f / DM);
      mm0 = pack2(m0, m0); mm1 = pack2(m1, m1);
      r0 = m0 * m0; r1 = m1 * m1;
      center<4>(xa + 140, mm0, mm1);
      center<16>(xa, mm0, mm1);
      const uint32_t ax = sb + OFF_AX + wg * 2048 + wi * 512 + lane * 4;
      sts32(ax, xa[140]); sts32(ax + 256, xa[141]); sts32(ax + 128, xa[142]); sts32(ax + 384, xa[143]);
      if (computed(s0)) {
        if (wg == 0) { if (lane < 8) mbar_arrive_cl(ebar + 8 * (4 + (lane >> 1)), lane < 6 ? 2 : 1); }
        else if (lane < 2) mbar_arrive_cl(ebar + 8 * 8, 2);
        else if (lane == 2) mbar_arrive(bars + BAR_XDONE);
      }
    }
    const uint32_t dax = desc_lo(sb + OFF_AX + wg * 2048, 128);
    const uint32_t d128 = desc_lo(sb, 8192);
    const uint32_t qrow = sb + OFF_QKV + (warp * 16 + (lane & 15)) * QPITCH + (lane >> 4) * 16 + c * 16;
#define P1_REL(K) { wg_wait<rl - 1>(); if (lane < 2 && !(first && (K) >= ppk - 2 && (K) < ppk && wg == 1)) mbar_arrive_cl1(ebar + 8 * (K)); }
#define P1_MAIN(PARITY, MMA, PPK, TILE, PRE)                                            \
    uint32_t rdy = 0;                                                               \
    static_for<0, 9>([&](auto KB) {                                                 \
      constexpr int kb = decltype(KB)::value, ppk = PPK;                            \
      constexpr bool first = TILE == 1, second = TILE == 2;                         \
      constexpr int rl = first ? 3 : 2;                                               \
      if constexpr (kb == ppk) {                                                    \
        P1_REL(kb - rl)                                                             \
        if (wg == 1) {                                                              \
          if constexpr (first) { wg_wait<0>(); if (lane < 4) mbar_arrive_cl1(ebar + 8 * (kb - 2 + (lane >> 1))); } \
          named_sync(4, 256);                                                       \
        }                                                                           \
      }                                                                             \
      if (kb == 0 || !rdy) mbar_spin(bars + BAR_FULL + 8 * kb, (PARITY));           \
      if constexpr (kb >= rl && kb != ppk) P1_REL(kb - rl)                          \
      wg_fence();                                                                   \
      static_for<0, 4>([&](auto I) {                                                \
        constexpr int i = decltype(I)::value;                                       \
        const uint32_t* a = xa + 16 * kb + 4 * i;                                   \
        if constexpr (kb == 8 && i == 3) { MMA##_SS; } else { MMA; }                \
        if constexpr (first && i == 0 && kb < 8) { center<kb < 7 ? 16 : 12>(xa + 16 * (kb + 1), mm0, mm1); wg_fence(); } \
        if constexpr (second && i == 2 && kb < 8) { scale<kb < 7 ? 16 : 12>(xa + 16 * (kb < 8 ? kb + 1 : 0), mm0, mm1); wg_fence(); } \
        if constexpr (i == 1 && kb < 8) rdy = mbar_test(bars + BAR_FULL + 8 * (kb + 1), (PARITY)); \
      });                                                                           \
      wg_commit();                                                                  \
      if constexpr (kb == 8) { if (wg == 0) named_arrive(4, 256); if constexpr (first) P1_REL(6) } \
      if constexpr (kb == 2 && first) {      \
        asm volatile("fence.proxy.async.shared::cta;" ::: "memory");                \
        named_sync(2 + wg, 128);                                                    \
      }                                                                             \
    });                                                                             \
    PRE                                                                             \
    wg_wait<1>(); if (lane < 2) mbar_arrive_cl1(ebar + 8 * 7);                      \
    wg_wait<0>();                                                                   \
    if (TILE != 1 && lane < 2) mbar_arrive_cl1(ebar + 8 * 8);
#define MMA128 (wgmma_n128<kb * SLOT + i * 2048, HI128>(acc, a[0], a[1], a[2], a[3], d128, kb + i))
#define MMA128_SS (wgmma_ss_n128<kb * SLOT + i * 2048, HI128>(acc, dax, d128))
    {
      float acc[64];
#define SCALES { mbar_spin(bars + BAR_STAT + 8 * wg, 0);                                     \
        const uint32_t a = sb + OFF_HALO + (warp >> 1) * QPITCH + (wi & 1) * 64 + (tid_now() & 28); \
        r0 = rsqrtf(fmaxf(__uint_as_float(lds32(a)) * (1.0f / DM) - r0, 0.f) + 1e-5f);       \
        r1 = rsqrtf(fmaxf(__uint_as_float(lds32(a + 32)) * (1.0f / DM) - r1, 0.f) + 1e-5f); \
        r0 *= 0.5f; r1 *= 0.5f; mm0 = pack2(r0, r0); mm1 = pack2(r1, r1);           \
        y[0] = lds32(ax); y[1] = lds32(ax + 256); y[2] = lds32(ax + 128); y[3] = lds32(ax + 384); scale<4>(y, mm0, mm1); }
      const uint32_t ax = sb + OFF_AX + warp * 512 + (tid_now() & 31) * 4;
      uint32_t y[4];
      P1_MAIN(0, MMA128, 6, 1, SCALES)
      keep<64>(acc);
      sts32(ax, y[0]); sts32(ax + 256, y[1]); sts32(ax + 128, y[2]); sts32(ax + 384, y[3]);
      asm volatile("fence.proxy.async.shared::cta;" ::: "memory");
      __syncwarp();
      if (lane < 2) mbar_arrive_cl1(ebar + 8 * 8);
#pragma unroll
      for (int j = 0; j < 8; j++) stsm_scaled(qrow + (j >> 2) * 144 + (j & 3) * 32, acc + 8 * j, r0, r1);
    }
    const uint64_t dq = desc64<HI128>(d128);
#pragma unroll 1
    do {
      const uint64_t d128 = dq + blockIdx.y, dtail = desc64<HI0>(desc_lo(sb + 8192, 128)) + blockIdx.y;
      float av[32], at[12];
#define MMAQ2 (wgmma_n64<kb * SLOT + i * 2048, HI128>(av, a[0], a[1], a[2], a[3], d128, kb + i), \
               wgmma_n24<kb * SLOT + i * 256, HI0>(at, a[0], a[1], a[2], a[3], dtail, kb + i))
#define MMAQ2_SS (wgmma_ss_n64<kb * SLOT + i * 2048, HI128>(av, dax, d128), wgmma_ss_n24<kb * SLOT + i * 256, HI0>(at, dax, dtail))
      scale<16>(xa, mm0, mm1);
      P1_MAIN(1, MMAQ2, 6, 2, )
      keep<32>(av); keep<12>(at);
#pragma unroll
      for (int j = 0; j < 4; j++) stsm_scaled(qrow + 288 + j * 32, av + 8 * j);
      const uint32_t qtail = qrow + 128 - c * 144;
      stsm_scaled(qtail + (tid_now() & 16) * 8, at);
      asm volatile("stmatrix.sync.aligned.m8n8.x2.shared.b16 [%0], {%1,%2};" ::"r"(qtail + 288), "r"(pack2(at[8], at[9])),
                   "r"(pack2(at[10], at[11])) : "memory");
      __syncwarp();
      if (lane == 0) mbar_arrive(bars + (wg ? BAR_QKV1 : BAR_QKV0));
    } while (blockIdx.y);
    uint4* const a2u = g_s.a2 + ((m * 4 + s) * 8 + warp) * NP2 * 32;
    uint4* hp = a2u + (c ? 77 : 2) * 32 + (tid_now() & 31);
#pragma unroll 1
    for (int t = 2; t < 10; t++) {
      float acc[64];
      const uint64_t d128 = dq + (t >> 8);
      P1_MAIN(t & 1, MMA128, 5, 0, )
      keep<64>(acc);
#pragma unroll
      for (int i = 0; i < 4; i++) {
        uint4 v;
        v.x = pack2(glu(acc[8 * i], acc[32 + 8 * i]), glu(acc[8 * i + 1], acc[32 + 8 * i + 1]));
        v.y = pack2(glu(acc[8 * i + 2], acc[32 + 8 * i + 2]), glu(acc[8 * i + 3], acc[32 + 8 * i + 3]));
        v.z = pack2(glu(acc[8 * i + 4], acc[32 + 8 * i + 4]), glu(acc[8 * i + 5], acc[32 + 8 * i + 5]));
        v.w = pack2(glu(acc[8 * i + 6], acc[32 + 8 * i + 6]), glu(acc[8 * i + 7], acc[32 + 8 * i + 7]));
        hp[i * 32] = v;
      }
      hp += c ? -128 : 128;
      if (t == 5) { __syncwarp(); if (lane == 0) mbar_arrive(bars + BAR_H5); }
    }
    uint4 af[6];
    const uint32_t ast = sb + OFF_AST + warp * AST_WARP + (tid_now() & 31) * 16;
    {
      float ag[24], au[24];
      const uint32_t d96 = d128 + 2 * c;
#define MMA96 (wgmma_n48<kb * SLOT + i * 2048, HI128>(ag, a[0], a[1], a[2], a[3], d96, kb + i), \
               wgmma_n48<kb * SLOT + i * 2048 + 8192, HI128>(au, a[0], a[1], a[2], a[3], d96, kb + i))
#define MMA96_SS (wgmma_ss_n48<kb * SLOT + i * 2048, HI128>(ag, dax, d96), wgmma_ss_n48<kb * SLOT + i * 2048 + 8192, HI128>(au, dax, d96))
      P1_MAIN(0, MMA96, 5, 0, mbar_spin(bars + BAR_STG, 0); af[0] = lds128(ast); af[1] = lds128(ast + 512);)
      keep<24>(ag); keep<24>(au);
      hp = a2u + (c ? 46 : 34) * 32 + (tid_now() & 31);
#pragma unroll
      for (int i = 0; i < 3; i++) {
        uint4 v;
        v.x = pack2(glu(ag[8 * i], au[8 * i]), glu(ag[8 * i + 1], au[8 * i + 1]));
        v.y = pack2(glu(ag[8 * i + 2], au[8 * i + 2]), glu(ag[8 * i + 3], au[8 * i + 3]));
        v.z = pack2(glu(ag[8 * i + 4], au[8 * i + 4]), glu(ag[8 * i + 5], au[8 * i + 5]));
        v.w = pack2(glu(ag[8 * i + 6], au[8 * i + 6]), glu(ag[8 * i + 7], au[8 * i + 7]));
        hp[i * 32] = v;
      }
    }
    __syncwarp();
    if (lane == 0) mbar_arrive(bars + BAR_HDONE);

    float oa[80], ob[64];
    const int dslot = c ? -64 : 64;
    const uint4* ap = a2u + (c ? 65 : 16) * 32 + (tid_now() & 31);
    const uint32_t da64 = desc_lo(sb + (c ? 0 : 4096), 1024), db64 = desc_lo(sb + (c ? 5120 : 0), 1024);
    uint32_t eb = 0;
    int dep = 3;
    int rb = 0, par = 1, ast_cur = 0;
    mbar_spin(bars + BAR_FULL, 1);
#define MMA_A(O, A, D, ACC) wgmma_n160<(O), HI64>(oa, (A).x, (A).y, (A).z, (A).w, D, ACC);
#define MMA_B(O, A, D, ACC) wgmma_n128<(O), HI64>(ob, (A).x, (A).y, (A).z, (A).w, D, ACC);
#pragma unroll 1
    for (int it = 0; it < 11; it++) {
      const uint64_t da = desc64<HI64>(da64) + rb * (SLOT >> 4), db = desc64<HI64>(db64) + rb * (SLOT >> 4);
      const uint32_t eprev = eb + 16;
      eb = ebar + 8 * rb;
      const int rn = rb == 6 ? 0 : rb + 3, pn = rb == 6 ? par ^ 1 : par;
      static_for<0, 3>([&](auto U) {
        constexpr int u = decltype(U)::value, v = (u + 1) % 3;
        wg_fence();
        MMA_A(u * SLOT, af[2 * u], da, u ? 1 : it)
        wg_commit();
        wg_wait<1>();
        if (lane < 2 && (u > 0 || it > 0)) mbar_arrive_cl1(u > 0 ? eb + 8 * (u - 1) : eprev);
        const uint32_t ast_w = ast_cur;
        ast_cur = ast_cur == 6144 ? 0 : ast_cur + 1024;
        asm volatile("cp.async.wait_group 5;" ::: "memory");
        af[2 * v] = lds128(ast + ast_cur);
        af[2 * v + 1] = lds128(ast + ast_cur + 512);
        wg_fence();
        MMA_B(u * SLOT, af[2 * u], db, u ? 1 : it)
        if (u == 0 && it == dep) {
          mbar_spin(bars + BAR_DEPS - 8 + 8 * (it >> 1), 0);
          dep = it == 3 ? 5 : 10;
          if (it == 10) cp_async16(ast + 7168, ap + (c ? -5 : 6) * 32);
        }
        cp_async16(ast + ast_w, ap);
        cp_async16(ast + ast_w + 512, ap + 32);
        asm volatile("cp.async.commit_group;" ::: "memory");
        ap += dslot;
        wg_fence();
        MMA_A(u * SLOT + 9216, af[2 * u + 1], da, 1)
        const uint32_t rdy = mbar_test(bars + BAR_FULL + 8 * (u < 2 ? rb + u + 1 : rn), u < 2 ? par : pn);
        MMA_B(u * SLOT + 9216, af[2 * u + 1], db, 1)
        wg_commit();
        if (!rdy) mbar_spin(bars + BAR_FULL + 8 * (u < 2 ? rb + u + 1 : rn), u < 2 ? par : pn);
      });
      rb = rn; par = pn;
    }
    auto tail = [&](auto CC) {
      constexpr int cc = decltype(CC)::value;
      float pa[80], pb[64];
      uint4 aw[15];
      uint32_t rdy = 0;
#define B_BAR(STEP) (bars + BAR_FULL + 8 * (((STEP) >> 1) % 9)), ((STEP) >= 72)
#define A_LOAD(LO, HI_)                                                                         \
      asm volatile("cp.async.wait_group %0;" ::"n"((80 - (HI_)) / 2) : "memory");               \
      static_for<LO, HI_>([&](auto I) { constexpr int i = decltype(I)::value; aw[i - 66] = lds128(ast + ((i >> 1) % 7) * 1024 + (i & 1) * 512); });
#define ACC(P) ((P) < 2 ? pb + ((P) & 1) * 32 : (P) < 4 ? pa + ((P) & 1) * 32 + cc * 16 : pa + (cc ? 0 : 64))
#define PASS(P, LO, HI_)                                                                        \
      static_for<LO, HI_>([&](auto I) {                                                         \
        constexpr int i = decltype(I)::value, p = P, st = 66 + i, o = (st >> 1) % 9 * SLOT + (st & 1) * 9216; \
        if constexpr (p == 0 && st % 2 == 0 && i > 0 && st < 80) { if (!rdy) mbar_spin(B_BAR(st)); wg_fence(); } \
        if constexpr (p == 0 && st == 80) { mbar_spin(bars + BAR_AXW, 0); wg_fence(); }         \
        if constexpr (p == 2 && st == 80) { mbar_spin(B_BAR(st)); wg_fence(); }                 \
        if constexpr (p < 2) wgmma_n64<(st < 80 ? o : OFF_AX - cc * 5120) + (p & 1) * 2048, HI64>(ACC(p), aw[i].x, aw[i].y, aw[i].z, aw[i].w, db64, 1); \
        else if constexpr (p < 4) wgmma_n64<o + (p & 1) * 2048 + cc * 1024, HI64>(ACC(p), aw[i].x, aw[i].y, aw[i].z, aw[i].w, da64, 1); \
        else wgmma_n32<o + (cc ? 0 : 4096), HI64>(ACC(p), aw[i].x, aw[i].y, aw[i].z, aw[i].w, da64, 1); \
        if constexpr (p == 4 && i == 2) { if (wg == 0) named_arrive(4, 256); }                  \
        if constexpr (p == 0 && st % 2 == 0 && st < 78) rdy = mbar_test(B_BAR(st + 2));         \
      });
#define STSM(ADDR, D) asm volatile("stmatrix.sync.aligned.m8n8.x4.shared.b16 [%0], {%1,%2,%3,%4};" ::"r"(ADDR),           \
          "r"(pack2((D)[0], (D)[1])), "r"(pack2((D)[2], (D)[3])), "r"(pack2((D)[4], (D)[5])), "r"(pack2((D)[6], (D)[7])) : "memory")
#define STAGE(P, ADDR, LO)                                                                      \
      {                                                                                         \
        constexpr int n = P < 4 ? 4 : 2, q = P < 3 ? (LO) + 3 : P == 3 ? 4 : 15, r = P < 3 ? 1 : P == 3 ? 2 : 0; \
        if constexpr (P < 4) { PASS(P + 1, LO, q) wg_commit(); }                                \
        if constexpr (P == 0) named_sync(2 + wg, 128);     \
        if constexpr (P == 3) { if (wg == 0) named_sync(7, 256); }                              \
        wg_wait<(P < 4)>();                                                                     \
        keep<8 * n>(ACC(P));                                                                    \
                                   \
        static_for<0, n>([&](auto J) {                                                          \
          constexpr int j = decltype(J)::value;                                                 \
          STSM((ADDR) ^ (j << 5), ACC(P) + 8 * j);                                              \
          if constexpr (j == n - 1) { __syncwarp(); if (lane == 0) mbar_arrive(bars + BAR_FL + 40 * wg + 8 * P); __syncwarp(); } \
          PASS(P + 1, q + j * r, (j == n - 1 ? 15 : q + (j + 1) * r))                           \
        });                                                                                     \
        if constexpr (P < 4) wg_commit();                                                       \
      }
      const uint32_t row = wi * 16 + (lane & 15), stg = sb + OFF_AST + wg * 4 * AST_WARP;
      const uint32_t s128 = stg + row * 128 + (((row & 7) ^ (lane >> 4)) << 4);
      aw[0] = af[0]; aw[1] = af[1];
      wg_wait<0>();
      rename<64>(pb, ob); rename<80>(pa, oa);
      if (wg == 1) named_arrive(7, 256);
      A_LOAD(68, 74)
      if (wg == 1) named_sync(4, 256);
      wg_fence();
      PASS(0, 0, 4)
      A_LOAD(74, 78)
      aw[14] = lds128(ast + 7168);
      PASS(0, 4, 10)
      A_LOAD(78, 80)
      PASS(0, 10, 12)
      PASS(0, 14, 15)
      PASS(1, 0, 3)
      PASS(0, 12, 14)
      wg_commit();
      STAGE(0, s128, 3)
      STAGE(1, s128 + 8192, 0)
      STAGE(2, s128 + 16384, 0)
      STAGE(3, s128 - stg + sb + 5 * SLOT + wg * 8192, 0)
      STAGE(4, stg + 24576 + row * 64 + ((((row >> 1) & 3) ^ (lane >> 4)) << 4), 0)
    };
    if (c) tail(std::integral_constant<int, 1>{}); else tail(std::integral_constant<int, 0>{});
  }
}

typedef CUresult (*EncodeFn)(CUtensorMap*, CUtensorMapDataType, cuuint32_t, void*, const cuuint64_t*, const cuuint64_t*,
                             const cuuint32_t*, const cuuint32_t*, CUtensorMapInterleave, CUtensorMapSwizzle,
                             CUtensorMapL2promotion, CUtensorMapFloatOOBfill);

void encode(EncodeFn fn, CUtensorMap* mp, const void* base, int rank, uint64_t d0, uint64_t d1, uint64_t d2, uint64_t s1,
            uint64_t s2, uint32_t b0, uint32_t b1, uint32_t b2, CUtensorMapSwizzle swz,
            CUtensorMapL2promotion promo = CU_TENSOR_MAP_L2_PROMOTION_L2_256B) {
  cuuint64_t dims[3] = {d0, d1, d2}, strides[2] = {s1, s2};
  cuuint32_t box[3] = {b0, b1, b2}, es[3] = {1, 1, 1};
  fn(mp, CU_TENSOR_MAP_DATA_TYPE_BFLOAT16, rank, const_cast<void*>(base), dims, strides, box, es,
     CU_TENSOR_MAP_INTERLEAVE_NONE, swz, promo, CU_TENSOR_MAP_FLOAT_OOB_FILL_NONE);
}

}

extern "C" void kernel_launch(void* const* d_in, const int* in_sizes, int n_in, void* d_out, int out_size) {
  (void)in_sizes; (void)n_in; (void)out_size;
  const void *x = d_in[0], *wqkv = d_in[1], *wo = d_in[2], *wgate = d_in[4], *wup = d_in[5], *wdown = d_in[6];
  EncodeFn fn = nullptr;
  cudaDriverEntryPointQueryResult qr;
  cudaGetDriverEntryPoint("cuTensorMapEncodeTiled", (void**)&fn, cudaEnableDefault, &qr);
  Params P;
  encode(fn, &P.wqkv, wqkv, 2, 3 * DM, DM, 1, 3 * DM * 2, 0, 64, 64, 1, CU_TENSOR_MAP_SWIZZLE_128B);
  encode(fn, &P.wtail, wqkv, 3, DM, DM, 3, 3 * DM * 2, DM * 2, 8, 64, 1, CU_TENSOR_MAP_SWIZZLE_NONE);
  encode(fn, &P.wg, wgate, 2, FF, DM, 1, FF * 2, 0, 64, 64, 1, CU_TENSOR_MAP_SWIZZLE_128B);
  encode(fn, &P.wu, wup, 2, FF, DM, 1, FF * 2, 0, 64, 64, 1, CU_TENSOR_MAP_SWIZZLE_128B);
  encode(fn, &P.wd, wdown, 3, 32, FF, 18, DM * 2, 64, 32, 16, 9, CU_TENSOR_MAP_SWIZZLE_64B, CU_TENSOR_MAP_L2_PROMOTION_L2_64B);
  encode(fn, &P.wo, wo, 3, 32, DM, 18, DM * 2, 64, 32, 16, 9, CU_TENSOR_MAP_SWIZZLE_64B, CU_TENSOR_MAP_L2_PROMOTION_L2_64B);
  encode(fn, &P.out128, d_out, 2, DM, SEQ, 1, DM * 2, 0, 64, 64, 1, CU_TENSOR_MAP_SWIZZLE_128B);
  encode(fn, &P.out64, d_out, 2, DM, SEQ, 1, DM * 2, 0, 32, 64, 1, CU_TENSOR_MAP_SWIZZLE_64B);
  encode(fn, &P.wg32, wgate, 2, FF, DM, 1, FF * 2, 0, 32, 64, 1, CU_TENSOR_MAP_SWIZZLE_64B, CU_TENSOR_MAP_L2_PROMOTION_L2_64B);
  encode(fn, &P.wu32, wup, 2, FF, DM, 1, FF * 2, 0, 32, 64, 1, CU_TENSOR_MAP_SWIZZLE_64B, CU_TENSOR_MAP_L2_PROMOTION_L2_64B);
  encode(fn, &P.wd4, wdown, 3, 32, FF, 18, DM * 2, 64, 32, 16, 4, CU_TENSOR_MAP_SWIZZLE_64B, CU_TENSOR_MAP_L2_PROMOTION_L2_64B);
  static int all_fit = -1;
  if (all_fit < 0) {
    cudaFuncSetAttribute(fused_kernel<false>, cudaFuncAttributeMaxDynamicSharedMemorySize, SMEM_BYTES);
    cudaFuncSetAttribute(fused_kernel<true>, cudaFuncAttributeMaxDynamicSharedMemorySize, SMEM_BYTES);
    cudaLaunchConfig_t cfg = {};
    cudaLaunchAttribute at;
    at.id = cudaLaunchAttributeClusterDimension; at.val.clusterDim.x = 2; at.val.clusterDim.y = 1; at.val.clusterDim.z = 1;
    cfg.gridDim = dim3(132); cfg.blockDim = dim3(384); cfg.dynamicSmemBytes = SMEM_BYTES; cfg.attrs = &at; cfg.numAttrs = 1;
    int n = 0;
    all_fit = cudaOccupancyMaxActiveClusters(&n, fused_kernel<false>, &cfg) == cudaSuccess && n >= 66;
  }
  (all_fit ? fused_kernel<false> : fused_kernel<true>)<<<132, 384, SMEM_BYTES, cudaStreamPerThread>>>((const __nv_bfloat16*)x, (__nv_bfloat16*)d_out, P);
}
```
